```python
import torch

def _softmax(x, axis=-1):
    return torch.softmax(x, dim=axis)
def _gelu(x):
    return torch.nn.functional.gelu(x, approximate="tanh")
def _silu(x):
    return torch.nn.functional.silu(x)
def _sigmoid(x):
    return torch.sigmoid(x)
def _layernorm(x, axis=-1, eps=1e-5):
    m = x.mean(dim=axis, keepdim=True)
    v = x.var(dim=axis, keepdim=True, unbiased=False)
    return (x - m) / torch.sqrt(v + eps)
def _scatter_add(tgt, idx, src, axis=0):
    return tgt.clone().index_add_(axis, idx, src)
def _segment_sum(src, seg, n):
    out = torch.zeros((n,) + src.shape[1:], dtype=src.dtype)
    return out.index_add_(0, seg, src)
def _pad(x, pw):
    flat = tuple(v for pair in reversed(pw) for v in pair)
    return torch.nn.functional.pad(x, flat)

kernel_name = 'parallel_sum__linear_attn_block__mixer_token_mlp__prompt'

def setup_inputs():

    _w = (lambda a: (lambda t: t.to(torch.bfloat16) if t.is_floating_point() else t)(torch.as_tensor(a)))
    def _A_setup():
        B, S, D = 1, 2048, 640
        return {
            "x": _w((lambda *s: torch.randn(*s, dtype=torch.bfloat16) * 0.05)(B, S, D)),
            "wqkv": _w((lambda *s: torch.randn(*s, dtype=torch.bfloat16) * 0.05)(D, 3 * D)),
            "wo": _w((lambda *s: torch.randn(*s, dtype=torch.bfloat16) * 0.05)(D, D)),
        }
    _A_in = _A_setup()

    def _B_setup():
        B, S, D, F = 1, 2048, 640, 1728
        return {
            "x": _w((lambda *s: torch.randn(*s, dtype=torch.bfloat16) * 0.05)(B, S, D)),
            "w1": _w((lambda *s: torch.randn(*s, dtype=torch.bfloat16) * 0.4)(S, F) * (S ** -0.5)),
            "b1": _w((lambda *s: torch.randn(*s, dtype=torch.bfloat16) * 3.2)(F) * 0.02),
            "w2": _w((lambda *s: torch.randn(*s, dtype=torch.bfloat16) * 0.2)(F, S) * (F ** -0.5)),
            "b2": _w((lambda *s: torch.randn(*s, dtype=torch.bfloat16) * 0.4)(S) * 0.02),
        }
    _B_in = _B_setup()

    return {
        "A_x": _A_in["x"],
        "A_wqkv": _A_in["wqkv"],
        "A_wo": _A_in["wo"],
        "B_x": _B_in["x"],
        "B_w1": _B_in["w1"],
        "B_b1": _B_in["b1"],
        "B_w2": _B_in["w2"],
        "B_b2": _B_in["b2"],
    }

def reference(A_x, A_wqkv, A_wo, B_x, B_w1, B_b1, B_w2, B_b2):
    def _A_ref(x, wqkv, wo):
        B, S, D = x.shape
        H = 32; Dh = D // H
        qkv = (lambda x, *d: x.permute(*d))((x @ wqkv).reshape(B, S, 3, H, Dh), 2, 0, 3, 1, 4)
        q, k, v = qkv[0], qkv[1], qkv[2]
        phi = lambda t: torch.where(t > 0, t + 1, torch.exp(t)) + 1e-6
        pq, pk = phi(q), phi(k)
        kv = torch.einsum("bhsd,bhse->bhde", pk, v)
        z = torch.einsum("bhsd->bhd", pk)
        num = torch.einsum("bhqd,bhde->bhqe", pq, kv)
        den = torch.einsum("bhqd,bhd->bhq", pq, z)[..., None] + 1e-6
        o = num / den
        return (lambda x, *d: x.permute(*d))(o, 0, 2, 1, 3).reshape(B, S, D) @ wo

    def _B_ref(x, w1, b1, w2, b2):
        B, S, D = x.shape
        h = _layernorm(x, axis=-1)
        u = torch.einsum("bsd,sf->bdf", h, w1) + b1
        u = _gelu(u)
        y = torch.einsum("bdf,fs->bds", u, w2) + b2
        return (lambda x, *d: x.permute(*d))(y, 0, 2, 1)

    x = A_x
    xn = _layernorm(x, axis=-1)
    return x + _A_ref(xn, A_wqkv, A_wo) + _B_ref(xn, B_w1, B_b1, B_w2, B_b2)
```

```cpp
#include <cuda_runtime.h>
#include <cuda.h>
#include <cuda_bf16.h>
#include <stdint.h>

namespace {

constexpr int S_ = 2048, D_ = 640, F_ = 1728, KF_ = 2368;
constexpr int NSTAGE = 4;
constexpr int STAGE_BYTES = 49152;
constexpr int B_OFF = 16384;
constexpr int PQ_PITCH = 88;
constexpr int SM_PQ = NSTAGE * STAGE_BYTES;
constexpr int SM_CS = SM_PQ + 128 * PQ_PITCH * 2;
constexpr int SM_STATS = SM_CS + 240 * 4;
constexpr int SM_KVF = SM_STATS + 128 * 8;
constexpr int SM_BAR = SM_KVF + 27 * 256;
constexpr int SM_TOTAL = SM_BAR + 256;
constexpr int SMEM_ALLOC = SM_TOTAL + 1024;

__device__ __align__(1024) __nv_bfloat16 g_h[S_ * D_];
__device__ __align__(1024) __nv_bfloat16 g_BF[D_ * KF_];
__device__ __align__(1024) __nv_bfloat16 g_o[S_ * D_];
__device__ float2 g_stats[S_];
__device__ float g_cs_part[16][1920];
__device__ float4 g_upart[135 * 3 * 8 * 256];
__device__ float g_kvpart[8][16][1920];
__device__ float g_kvfin[8][1920];
__device__ float4 g_fpart[64 * 20 * 256];

struct Counters {
    unsigned hk[32];
    unsigned cs[8];
    unsigned wo;
    unsigned uflag[45];
    unsigned gflag[45];
    unsigned kv[8];
    unsigned kv2[8];
    unsigned o[16];
    unsigned fflag[64];
    unsigned done;
};
__device__ Counters g_cnt;
#define FAIL(code) __trap()
#define MBAR_LIMIT (1u << 24)
#define SPIN_LIMIT (1u << 22)
#define PROF(i)

__device__ __forceinline__ uint32_t smem_u32(const void* p) { return (uint32_t)__cvta_generic_to_shared(p); }
__device__ __forceinline__ void mbar_init(uint32_t bar, uint32_t cnt) { asm volatile("mbarrier.init.shared::cta.b64 [%0], %1;" ::"r"(bar), "r"(cnt)); }
__device__ __forceinline__ void mbar_expect_tx(uint32_t bar, uint32_t bytes) { asm volatile("mbarrier.arrive.expect_tx.shared::cta.b64 _, [%0], %1;" ::"r"(bar), "r"(bytes) : "memory"); }
__device__ __forceinline__ void mbar_arrive(uint32_t bar) { asm volatile("mbarrier.arrive.shared::cta.b64 _, [%0];" ::"r"(bar) : "memory"); }
__device__ __forceinline__ void mbar_wait(uint32_t bar, uint32_t parity) {
    uint32_t done = 0;
    for (uint32_t i = 0; i < MBAR_LIMIT; i++) {
        asm volatile("{\n.reg .pred p;\nmbarrier.try_wait.parity.shared::cta.b64 p, [%1], %2;\nselp.u32 %0, 1, 0, p;\n}" : "=r"(done) : "r"(bar), "r"(parity) : "memory");
        if (done) return;
    }
    FAIL(100 + ((bar >> 3) & 15));
}
__device__ __forceinline__ void tma2d(uint32_t dst, const CUtensorMap* m, uint32_t bar, int c0, int c1) {
    asm volatile("cp.async.bulk.tensor.2d.shared::cluster.global.mbarrier::complete_tx::bytes [%0], [%1, {%3, %4}], [%2];"
                 ::"r"(dst), "l"((uint64_t)m), "r"(bar), "r"(c0), "r"(c1) : "memory");
}
__device__ __forceinline__ void tma3d(uint32_t dst, const CUtensorMap* m, uint32_t bar, int c0, int c1, int c2) {
    asm volatile("cp.async.bulk.tensor.3d.shared::cluster.global.mbarrier::complete_tx::bytes [%0], [%1, {%3, %4, %5}], [%2];"
                 ::"r"(dst), "l"((uint64_t)m), "r"(bar), "r"(c0), "r"(c1), "r"(c2) : "memory");
}
__device__ __forceinline__ unsigned ld_acquire(const unsigned* p) {
    unsigned v;
    asm volatile("ld.acquire.gpu.global.u32 %0, [%1];" : "=r"(v) : "l"(p) : "memory");
    return v;
}
__device__ __forceinline__ void red_release(unsigned* p, unsigned v) {
    asm volatile("red.release.gpu.global.add.u32 [%0], %1;" ::"l"(p), "r"(v) : "memory");
}
__device__ __forceinline__ void spin_ge(const unsigned* p, unsigned target) {
    for (uint32_t i = 0; i < SPIN_LIMIT; i++) {
        if (ld_acquire(p) >= target) return;
        __nanosleep(32);
    }
    FAIL(1000 + (int)(p - (const unsigned*)&g_cnt));
}
__device__ __forceinline__ void fence_proxy_async() { asm volatile("fence.proxy.async;" ::: "memory"); }
__device__ __forceinline__ void named_bar(int id, int n) { asm volatile("bar.sync %0, %1;" ::"r"(id), "r"(n) : "memory"); }
__device__ __forceinline__ void wg_fence() { asm volatile("wgmma.fence.sync.aligned;" ::: "memory"); }
__device__ __forceinline__ void wg_commit() { asm volatile("wgmma.commit_group.sync.aligned;" ::: "memory"); }
template <int N> __device__ __forceinline__ void wg_wait() { asm volatile("wgmma.wait_group.sync.aligned %0;" ::"n"(N) : "memory"); }
template <int R> __device__ __forceinline__ void reg_alloc() { asm volatile("setmaxnreg.inc.sync.aligned.u32 %0;" ::"n"(R)); }
template <int R> __device__ __forceinline__ void reg_dealloc() { asm volatile("setmaxnreg.dec.sync.aligned.u32 %0;" ::"n"(R)); }

__device__ __forceinline__ uint64_t desc_kmajor(uint32_t addr) {
    return (uint64_t)((addr & 0x3FFFF) >> 4) | ((uint64_t)1 << 16) | ((uint64_t)64 << 32) | ((uint64_t)1 << 62);
}
__device__ __forceinline__ uint64_t desc_mnmajor(uint32_t addr) {
    return (uint64_t)((addr & 0x3FFFF) >> 4) | ((uint64_t)512 << 16) | ((uint64_t)64 << 32) | ((uint64_t)1 << 62);
}
__device__ __forceinline__ uint32_t pack_bf16(float a, float b) {
    uint32_t r;
    asm("cvt.rn.bf16x2.f32 %0, %1, %2;" : "=r"(r) : "f"(b), "f"(a));
    return r;
}
__device__ __forceinline__ float bf_lo(uint32_t v) { return __uint_as_float(v << 16); }
__device__ __forceinline__ float bf_hi(uint32_t v) { return __uint_as_float(v & 0xFFFF0000u); }
__device__ __forceinline__ float warp_sum(float v) {
#pragma unroll
    for (int o = 16; o > 0; o >>= 1) v += __shfl_xor_sync(0xffffffffu, v, o);
    return v;
}
__device__ __forceinline__ void ldsm_x4(uint32_t (&r)[4], uint32_t addr) {
    asm volatile("ldmatrix.sync.aligned.m8n8.x4.shared.b16 {%0,%1,%2,%3}, [%4];" : "=r"(r[0]), "=r"(r[1]), "=r"(r[2]), "=r"(r[3]) : "r"(addr) : "memory");
}
__device__ __forceinline__ void ldsm_x4_t(uint32_t (&r)[4], uint32_t addr) {
    asm volatile("ldmatrix.sync.aligned.m8n8.x4.trans.shared.b16 {%0,%1,%2,%3}, [%4];" : "=r"(r[0]), "=r"(r[1]), "=r"(r[2]), "=r"(r[3]) : "r"(addr) : "memory");
}
__device__ __forceinline__ void ldsm_x2_t(uint32_t (&r)[2], uint32_t addr) {
    asm volatile("ldmatrix.sync.aligned.m8n8.x2.trans.shared.b16 {%0,%1}, [%2];" : "=r"(r[0]), "=r"(r[1]) : "r"(addr) : "memory");
}
__device__ __forceinline__ void mma16816(float (&c)[4], const uint32_t (&a)[4], uint32_t b0, uint32_t b1) {
    asm volatile("mma.sync.aligned.m16n8k16.row.col.f32.bf16.bf16.f32 {%0,%1,%2,%3}, {%4,%5,%6,%7}, {%8,%9}, {%0,%1,%2,%3};"
                 : "+f"(c[0]), "+f"(c[1]), "+f"(c[2]), "+f"(c[3]) : "r"(a[0]), "r"(a[1]), "r"(a[2]), "r"(a[3]), "r"(b0), "r"(b1));
}
__device__ __forceinline__ float gelu_tanh(float u) {
    float z = 1.5957691216057308f * (u + 0.044715f * u * u * u);
    return __fdividef(u, 1.0f + __expf(-z));
}

template<int TA, int TB>
__device__ __forceinline__ void wgmma_n160(float (&d)[120], uint64_t da, uint64_t db, int scale_d) {
    asm volatile("{\n.reg .pred p;\nsetp.ne.b32 p, %82, 0;\n"
        "wgmma.mma_async.sync.aligned.m64n160k16.f32.bf16.bf16 "
        "{%0, %1, %2, %3, %4, %5, %6, %7, %8, %9, %10, %11, %12, %13, %14, %15, "
        "%16, %17, %18, %19, %20, %21, %22, %23, %24, %25, %26, %27, %28, %29, %30, %31, "
        "%32, %33, %34, %35, %36, %37, %38, %39, %40, %41, %42, %43, %44, %45, %46, %47, "
        "%48, %49, %50, %51, %52, %53, %54, %55, %56, %57, %58, %59, %60, %61, %62, %63, "
        "%64, %65, %66, %67, %68, %69, %70, %71, %72, %73, %74, %75, %76, %77, %78, %79}, "
        "%80, %81, p, 1, 1, %83, %84;\n}\n"
        : "+f"(d[0]), "+f"(d[1]), "+f"(d[2]), "+f"(d[3]), "+f"(d[4]), "+f"(d[5]), "+f"(d[6]), "+f"(d[7]),
          "+f"(d[8]), "+f"(d[9]), "+f"(d[10]), "+f"(d[11]), "+f"(d[12]), "+f"(d[13]), "+f"(d[14]), "+f"(d[15]),
          "+f"(d[16]), "+f"(d[17]), "+f"(d[18]), "+f"(d[19]), "+f"(d[20]), "+f"(d[21]), "+f"(d[22]), "+f"(d[23]),
          "+f"(d[24]), "+f"(d[25]), "+f"(d[26]), "+f"(d[27]), "+f"(d[28]), "+f"(d[29]), "+f"(d[30]), "+f"(d[31]),
          "+f"(d[32]), "+f"(d[33]), "+f"(d[34]), "+f"(d[35]), "+f"(d[36]), "+f"(d[37]), "+f"(d[38]), "+f"(d[39]),
          "+f"(d[40]), "+f"(d[41]), "+f"(d[42]), "+f"(d[43]), "+f"(d[44]), "+f"(d[45]), "+f"(d[46]), "+f"(d[47]),
          "+f"(d[48]), "+f"(d[49]), "+f"(d[50]), "+f"(d[51]), "+f"(d[52]), "+f"(d[53]), "+f"(d[54]), "+f"(d[55]),
          "+f"(d[56]), "+f"(d[57]), "+f"(d[58]), "+f"(d[59]), "+f"(d[60]), "+f"(d[61]), "+f"(d[62]), "+f"(d[63]),
          "+f"(d[64]), "+f"(d[65]), "+f"(d[66]), "+f"(d[67]), "+f"(d[68]), "+f"(d[69]), "+f"(d[70]), "+f"(d[71]),
          "+f"(d[72]), "+f"(d[73]), "+f"(d[74]), "+f"(d[75]), "+f"(d[76]), "+f"(d[77]), "+f"(d[78]), "+f"(d[79])
        : "l"(da), "l"(db), "r"(scale_d), "n"(TA), "n"(TB));
}

template<int TA, int TB>
__device__ __forceinline__ void wgmma_n192(float (&d)[120], uint64_t da, uint64_t db, int scale_d) {
    asm volatile("{\n.reg .pred p;\nsetp.ne.b32 p, %98, 0;\n"
        "wgmma.mma_async.sync.aligned.m64n192k16.f32.bf16.bf16 "
        "{%0, %1, %2, %3, %4, %5, %6, %7, %8, %9, %10, %11, %12, %13, %14, %15, "
        "%16, %17, %18, %19, %20, %21, %22, %23, %24, %25, %26, %27, %28, %29, %30, %31, "
        "%32, %33, %34, %35, %36, %37, %38, %39, %40, %41, %42, %43, %44, %45, %46, %47, "
        "%48, %49, %50, %51, %52, %53, %54, %55, %56, %57, %58, %59, %60, %61, %62, %63, "
        "%64, %65, %66, %67, %68, %69, %70, %71, %72, %73, %74, %75, %76, %77, %78, %79, "
        "%80, %81, %82, %83, %84, %85, %86, %87, %88, %89, %90, %91, %92, %93, %94, %95}, "
        "%96, %97, p, 1, 1, %99, %100;\n}\n"
        : "+f"(d[0]), "+f"(d[1]), "+f"(d[2]), "+f"(d[3]), "+f"(d[4]), "+f"(d[5]), "+f"(d[6]), "+f"(d[7]),
          "+f"(d[8]), "+f"(d[9]), "+f"(d[10]), "+f"(d[11]), "+f"(d[12]), "+f"(d[13]), "+f"(d[14]), "+f"(d[15]),
          "+f"(d[16]), "+f"(d[17]), "+f"(d[18]), "+f"(d[19]), "+f"(d[20]), "+f"(d[21]), "+f"(d[22]), "+f"(d[23]),
          "+f"(d[24]), "+f"(d[25]), "+f"(d[26]), "+f"(d[27]), "+f"(d[28]), "+f"(d[29]), "+f"(d[30]), "+f"(d[31]),
          "+f"(d[32]), "+f"(d[33]), "+f"(d[34]), "+f"(d[35]), "+f"(d[36]), "+f"(d[37]), "+f"(d[38]), "+f"(d[39]),
          "+f"(d[40]), "+f"(d[41]), "+f"(d[42]), "+f"(d[43]), "+f"(d[44]), "+f"(d[45]), "+f"(d[46]), "+f"(d[47]),
          "+f"(d[48]), "+f"(d[49]), "+f"(d[50]), "+f"(d[51]), "+f"(d[52]), "+f"(d[53]), "+f"(d[54]), "+f"(d[55]),
          "+f"(d[56]), "+f"(d[57]), "+f"(d[58]), "+f"(d[59]), "+f"(d[60]), "+f"(d[61]), "+f"(d[62]), "+f"(d[63]),
          "+f"(d[64]), "+f"(d[65]), "+f"(d[66]), "+f"(d[67]), "+f"(d[68]), "+f"(d[69]), "+f"(d[70]), "+f"(d[71]),
          "+f"(d[72]), "+f"(d[73]), "+f"(d[74]), "+f"(d[75]), "+f"(d[76]), "+f"(d[77]), "+f"(d[78]), "+f"(d[79]),
          "+f"(d[80]), "+f"(d[81]), "+f"(d[82]), "+f"(d[83]), "+f"(d[84]), "+f"(d[85]), "+f"(d[86]), "+f"(d[87]),
          "+f"(d[88]), "+f"(d[89]), "+f"(d[90]), "+f"(d[91]), "+f"(d[92]), "+f"(d[93]), "+f"(d[94]), "+f"(d[95])
        : "l"(da), "l"(db), "r"(scale_d), "n"(TA), "n"(TB));
}

template<int TA, int TB>
__device__ __forceinline__ void wgmma_n240(float (&d)[120], uint64_t da, uint64_t db, int scale_d) {
    asm volatile("{\n.reg .pred p;\nsetp.ne.b32 p, %122, 0;\n"
        "wgmma.mma_async.sync.aligned.m64n240k16.f32.bf16.bf16 "
        "{%0, %1, %2, %3, %4, %5, %6, %7, %8, %9, %10, %11, %12, %13, %14, %15, "
        "%16, %17, %18, %19, %20, %21, %22, %23, %24, %25, %26, %27, %28, %29, %30, %31, "
        "%32, %33, %34, %35, %36, %37, %38, %39, %40, %41, %42, %43, %44, %45, %46, %47, "
        "%48, %49, %50, %51, %52, %53, %54, %55, %56, %57, %58, %59, %60, %61, %62, %63, "
        "%64, %65, %66, %67, %68, %69, %70, %71, %72, %73, %74, %75, %76, %77, %78, %79, "
        "%80, %81, %82, %83, %84, %85, %86, %87, %88, %89, %90, %91, %92, %93, %94, %95, "
        "%96, %97, %98, %99, %100, %101, %102, %103, %104, %105, %106, %107, %108, %109, %110, %111, "
        "%112, %113, %114, %115, %116, %117, %118, %119}, "
        "%120, %121, p, 1, 1, %123, %124;\n}\n"
        : "+f"(d[0]), "+f"(d[1]), "+f"(d[2]), "+f"(d[3]), "+f"(d[4]), "+f"(d[5]), "+f"(d[6]), "+f"(d[7]),
          "+f"(d[8]), "+f"(d[9]), "+f"(d[10]), "+f"(d[11]), "+f"(d[12]), "+f"(d[13]), "+f"(d[14]), "+f"(d[15]),
          "+f"(d[16]), "+f"(d[17]), "+f"(d[18]), "+f"(d[19]), "+f"(d[20]), "+f"(d[21]), "+f"(d[22]), "+f"(d[23]),
          "+f"(d[24]), "+f"(d[25]), "+f"(d[26]), "+f"(d[27]), "+f"(d[28]), "+f"(d[29]), "+f"(d[30]), "+f"(d[31]),
          "+f"(d[32]), "+f"(d[33]), "+f"(d[34]), "+f"(d[35]), "+f"(d[36]), "+f"(d[37]), "+f"(d[38]), "+f"(d[39]),
          "+f"(d[40]), "+f"(d[41]), "+f"(d[42]), "+f"(d[43]), "+f"(d[44]), "+f"(d[45]), "+f"(d[46]), "+f"(d[47]),
          "+f"(d[48]), "+f"(d[49]), "+f"(d[50]), "+f"(d[51]), "+f"(d[52]), "+f"(d[53]), "+f"(d[54]), "+f"(d[55]),
          "+f"(d[56]), "+f"(d[57]), "+f"(d[58]), "+f"(d[59]), "+f"(d[60]), "+f"(d[61]), "+f"(d[62]), "+f"(d[63]),
          "+f"(d[64]), "+f"(d[65]), "+f"(d[66]), "+f"(d[67]), "+f"(d[68]), "+f"(d[69]), "+f"(d[70]), "+f"(d[71]),
          "+f"(d[72]), "+f"(d[73]), "+f"(d[74]), "+f"(d[75]), "+f"(d[76]), "+f"(d[77]), "+f"(d[78]), "+f"(d[79]),
          "+f"(d[80]), "+f"(d[81]), "+f"(d[82]), "+f"(d[83]), "+f"(d[84]), "+f"(d[85]), "+f"(d[86]), "+f"(d[87]),
          "+f"(d[88]), "+f"(d[89]), "+f"(d[90]), "+f"(d[91]), "+f"(d[92]), "+f"(d[93]), "+f"(d[94]), "+f"(d[95]),
          "+f"(d[96]), "+f"(d[97]), "+f"(d[98]), "+f"(d[99]), "+f"(d[100]), "+f"(d[101]), "+f"(d[102]), "+f"(d[103]),
          "+f"(d[104]), "+f"(d[105]), "+f"(d[106]), "+f"(d[107]), "+f"(d[108]), "+f"(d[109]), "+f"(d[110]), "+f"(d[111]),
          "+f"(d[112]), "+f"(d[113]), "+f"(d[114]), "+f"(d[115]), "+f"(d[116]), "+f"(d[117]), "+f"(d[118]), "+f"(d[119])
        : "l"(da), "l"(db), "r"(scale_d), "n"(TA), "n"(TB));
}

struct Params {
    const __nv_bfloat16* x;
    const __nv_bfloat16* wqkv;
    const __nv_bfloat16* wo;
    const __nv_bfloat16* b1;
    const __nv_bfloat16* b2;
    __nv_bfloat16* out;
};

struct G2Unit { int dt, ft, ks, kb0, nk, tile; };
__device__ __forceinline__ G2Unit g2_unit(int c, int round) {
    G2Unit u;
    if (round == 0) {
        int p = c >> 1, r = c & 1;
        if (p < 54) { int dp = p / 27, rem = p % 27; u.ft = rem / 3; u.ks = rem % 3; u.dt = 2 * dp + r; }
        else { int q = p - 54; u.ks = q % 3; u.dt = 4; u.ft = 2 * (q / 3) + r; }
    } else { u.dt = 4; u.ft = 8; u.ks = c - 128; }
    u.kb0 = u.ks * 11; u.nk = (u.ks == 2) ? 10 : 11; u.tile = u.dt * 9 + u.ft;
    return u;
}

__device__ __forceinline__ void g2_produce(const G2Unit& u, uint32_t sbase, uint32_t bar_full, uint32_t bar_empty, int& it, int pre,
                                           const CUtensorMap* mH, const CUtensorMap* mW1, int lane) {
    if (lane < u.nk) spin_ge(&g_cnt.hk[u.kb0 + lane], 64);
    __syncwarp();
    if (lane == 0) {
        fence_proxy_async();
        for (int k = 0; k < u.nk; k++, it++) {
            int s = it % NSTAGE;
            uint32_t st = sbase + s * STAGE_BYTES, fb = bar_full + s * 8;
            if (k >= pre) {
                mbar_wait(bar_empty + s * 8, ((it / NSTAGE) & 1) ^ 1);
                mbar_expect_tx(fb, 16384 + 24576);
                tma3d(st + B_OFF, mW1, fb, 0, (u.kb0 + k) * 64, u.ft * 3);
            }
            tma3d(st, mH, fb, 0, (u.kb0 + k) * 64, u.dt * 2);
        }
    } else {
        it += u.nk;
    }
    __syncwarp();
}

__device__ __forceinline__ void g2_consume(const G2Unit& u, uint32_t sbase, uint32_t bar_full, uint32_t bar_empty, int& it, float (&acc)[120], int wg, int ctid) {
    for (int k = 0; k < u.nk; k++, it++) {
        int s = it % NSTAGE;
        mbar_wait(bar_full + s * 8, (it / NSTAGE) & 1);
        uint32_t st = sbase + s * STAGE_BYTES;
        uint64_t da = desc_mnmajor(st + wg * 8192), db = desc_mnmajor(st + B_OFF);
        wg_fence();
#pragma unroll
        for (int kk = 0; kk < 4; kk++) wgmma_n192<1, 1>(acc, da + kk * 128, db + kk * 128, (k | kk) != 0);
        wg_commit();
        if (k > 0) { wg_wait<1>(); if ((ctid & 127) == 0) mbar_arrive(bar_empty + ((it - 1) % NSTAGE) * 8); }
    }
    wg_wait<0>();
    if ((ctid & 127) == 0) mbar_arrive(bar_empty + ((it - 1) % NSTAGE) * 8);
    float4* dst = g_upart + (size_t)(u.tile * 3 + u.ks) * (3 * 8 * 256) + ctid;
#pragma unroll
    for (int q = 0; q < 24; q++) dst[q * 256] = make_float4(acc[4 * q], acc[4 * q + 1], acc[4 * q + 2], acc[4 * q + 3]);
    __threadfence();
    named_bar(1, 256);
    if (ctid == 0) red_release(&g_cnt.uflag[u.tile], 1);
}

__device__ __forceinline__ void g2_finalize(const G2Unit& u, const __nv_bfloat16* b1, int atid) {
    if (atid == 0) spin_ge(&g_cnt.uflag[u.tile], 3);
    named_bar(2, 96);
    const float4* base = g_upart + (size_t)(u.tile * 3) * (3 * 8 * 256) + (size_t)u.ks * (8 * 256);
#pragma unroll 1
    for (int vt = atid; vt < 256; vt += 96) {
        int wg = vt >> 7, wp = (vt >> 5) & 3, ln = vt & 31;
        int row = u.dt * 128 + wg * 64 + wp * 16 + (ln >> 2);
        int colb = u.ft * 192 + u.ks * 64 + 2 * (ln & 3);
#pragma unroll
        for (int q = 0; q < 8; q++) {
            float4 a = __ldcg(base + q * 256 + vt);
            float4 b = __ldcg(base + 3 * 8 * 256 + q * 256 + vt);
            float4 c = __ldcg(base + 2 * 3 * 8 * 256 + q * 256 + vt);
            int col = colb + 8 * q;
            uint32_t bb = *(const uint32_t*)(b1 + col);
            float bl = bf_lo(bb), bh = bf_hi(bb);
            float u0 = gelu_tanh(a.x + b.x + c.x + bl), u1 = gelu_tanh(a.y + b.y + c.y + bh);
            float u2 = gelu_tanh(a.z + b.z + c.z + bl), u3 = gelu_tanh(a.w + b.w + c.w + bh);
            *(uint32_t*)(g_BF + (size_t)row * KF_ + col) = pack_bf16(u0, u1);
            *(uint32_t*)(g_BF + (size_t)(row + 8) * KF_ + col) = pack_bf16(u2, u3);
        }
    }
    fence_proxy_async();
    __threadfence();
    named_bar(2, 96);
    if (atid == 0) red_release(&g_cnt.gflag[u.tile], 1);
}

__global__ void __cluster_dims__(2, 1, 1) __launch_bounds__(384, 1)
mega_kernel(const __grid_constant__ CUtensorMap mX, const __grid_constant__ CUtensorMap mH, const __grid_constant__ CUtensorMap mW1,
            const __grid_constant__ CUtensorMap mW2, const __grid_constant__ CUtensorMap mO, const __grid_constant__ CUtensorMap mBF,
            const Params P) {
    extern __shared__ uint8_t smem_raw[];
    const uint32_t sbase = (smem_u32(smem_raw) + 1023) & ~1023u;
    uint8_t* sgen = smem_raw + (sbase - smem_u32(smem_raw));
    const uint32_t bar_full = sbase + SM_BAR, bar_empty = bar_full + 32, bar_fcp = bar_full + 64, bar_aux = bar_full + 96;
    const int tid = threadIdx.x, warp = tid >> 5, lane = tid & 31;
    const int c = blockIdx.x;
    const bool main_cta = c < 128;

    if (tid == 0) {
        for (int i = 0; i < NSTAGE; i++) { mbar_init(bar_full + i * 8, 1); mbar_init(bar_empty + i * 8, 2); mbar_init(bar_fcp + i * 8, 32); }
        mbar_init(bar_aux, 96);
        asm volatile("fence.mbarrier_init.release.cluster;" ::: "memory");
    }
    __syncthreads();

    const G2Unit u0 = g2_unit(c, 0);
    if (tid == 0) {
        for (int k = 0; k < NSTAGE; k++) {
            uint32_t fb = bar_full + k * 8;
            mbar_expect_tx(fb, 16384 + 24576);
            tma3d(sbase + k * STAGE_BYTES + B_OFF, &mW1, fb, 0, (u0.kb0 + k) * 64, u0.ft * 3);
        }
    }

    if (main_cta) {
        const int nrow = (warp >= 4 && warp < 8) ? 2 : 1;
        uint2 xv[2][5];
#pragma unroll
        for (int rr = 0; rr < 2; rr++) {
            if (rr < nrow) {
                const int row = c * 16 + (rr ? warp + 8 : warp);
                const uint2* xr = (const uint2*)(P.x + (size_t)row * D_);
#pragma unroll
                for (int i = 0; i < 5; i++) xv[rr][i] = __ldg(xr + lane + 32 * i);
            }
        }
#pragma unroll
        for (int rr = 0; rr < 2; rr++) {
            if (rr < nrow) {
                const int row = c * 16 + (rr ? warp + 8 : warp);
                float f[20];
#pragma unroll
                for (int i = 0; i < 5; i++) {
                    uint2 v = xv[rr][i];
                    f[4 * i] = bf_lo(v.x); f[4 * i + 1] = bf_hi(v.x); f[4 * i + 2] = bf_lo(v.y); f[4 * i + 3] = bf_hi(v.y);
                }
                float s = 0.f;
#pragma unroll
                for (int i = 0; i < 20; i++) s += f[i];
                const float mean = warp_sum(s) * (1.0f / D_);
                float q = 0.f;
#pragma unroll
                for (int i = 0; i < 20; i++) { f[i] -= mean; q += f[i] * f[i]; }
                const float rstd = rsqrtf(warp_sum(q) * (1.0f / D_) + 1e-5f);
                s = 0.f;
#pragma unroll
                for (int i = 0; i < 20; i += 2) {
                    uint32_t p = pack_bf16(f[i] * rstd, f[i + 1] * rstd);
                    f[i] = bf_lo(p); f[i + 1] = bf_hi(p);
                    s += f[i] + f[i + 1];
                }
                const float mean2 = warp_sum(s) * (1.0f / D_);
                q = 0.f;
#pragma unroll
                for (int i = 0; i < 20; i++) { f[i] -= mean2; q += f[i] * f[i]; }
                const float rstd2 = rsqrtf(warp_sum(q) * (1.0f / D_) + 1e-5f);
                uint2* hr = (uint2*)(g_h + (size_t)row * D_);
#pragma unroll
                for (int i = 0; i < 5; i++) {
                    uint2 v;
                    v.x = pack_bf16(f[4 * i] * rstd2, f[4 * i + 1] * rstd2);
                    v.y = pack_bf16(f[4 * i + 2] * rstd2, f[4 * i + 3] * rstd2);
                    hr[lane + 32 * i] = v;
                }
                if (lane == 0) g_stats[row] = make_float2(mean, rstd);
            }
        }
        fence_proxy_async();
        __threadfence();
        __syncwarp();
        if (lane == 0) red_release(&g_cnt.hk[c >> 2], nrow);
    }

    const int pr = c >> 1, rk = c & 1;
    const int g1_g = pr & 7, g1_m = 2 * ((pr >> 3) & 7) + rk;
    const int f_m = 2 * (pr & 7) + rk, f_n = (pr >> 3) & 3, f_hh = (pr >> 5) & 1;
    const int f_nw2 = f_hh ? 16 : 11, f_kb0 = f_hh ? 11 : 0, f_nk = f_hh ? 16 : 21;

    if (warp < 4) {
      reg_dealloc<96>();
      if (warp == 0) {
        int it = 0;
        g2_produce(u0, sbase, bar_full, bar_empty, it, NSTAGE, &mH, &mW1, lane);
        if (main_cta) {
            const __nv_bfloat16* wsrc = P.wqkv + (lane / 10) * 640 + g1_g * 80 + (lane % 10) * 8;
            const uint32_t cdst = B_OFF + (lane >> 3) * 8192;
            for (int k = 0; k < 10; k++, it++) {
                int s = it % NSTAGE;
                uint32_t st = sbase + s * STAGE_BYTES;
                mbar_wait(bar_empty + s * 8, ((it / NSTAGE) & 1) ^ 1);
                if (lane == 0) {
                    mbar_expect_tx(bar_full + s * 8, 16384);
                    tma2d(st, &mX, bar_full + s * 8, k * 64, g1_m * 128);
                }
                if (lane < 30) {
                    const __nv_bfloat16* src = wsrc + (size_t)(k * 64) * 1920;
#pragma unroll 8
                    for (int r = 0; r < 64; r++) {
                        uint32_t d = st + cdst + r * 128 + (((lane & 7) ^ (r & 7)) << 4);
                        asm volatile("cp.async.cg.shared.global [%0], [%1], 16;" ::"r"(d), "l"(src + (size_t)r * 1920) : "memory");
                    }
                }
                asm volatile("cp.async.mbarrier.arrive.noinc.shared::cta.b64 [%0];" ::"r"(bar_fcp + s * 8) : "memory");
            }
            if (lane == 0) {
                int s = it % NSTAGE;
                mbar_wait(bar_empty + s * 8, ((it / NSTAGE) & 1) ^ 1);
                mbar_arrive(bar_full + s * 8);
            }
            it++;
            const int dt0 = (f_n * 160) >> 7, dt1 = (f_n * 160 + 159) >> 7;
            for (int k = 0; k < f_nk; k++, it++) {
                int s = it % NSTAGE;
                uint32_t st = sbase + s * STAGE_BYTES, fb = bar_full + s * 8;
                if (k < f_nw2) {
                    int kb = f_kb0 + k;
                    if (k == 0 || kb % 3 == 0) {
                        if (lane < 2) spin_ge(&g_cnt.gflag[(lane ? dt1 : dt0) * 9 + kb / 3], 3);
                        __syncwarp();
                    }
                    if (lane == 0) {
                        fence_proxy_async();
                        mbar_wait(bar_empty + s * 8, ((it / NSTAGE) & 1) ^ 1);
                        mbar_expect_tx(fb, 16384 + 20480);
                        tma3d(st, &mW2, fb, 0, kb * 64, f_m * 2);
                        tma2d(st + B_OFF, &mBF, fb, kb * 64, f_n * 160);
                    }
                } else {
                    int ko = k - f_nw2;
                    if (ko == 0) {
                        if (lane == 0) spin_ge(&g_cnt.o[f_m], 8);
                        if (lane == 1) spin_ge(&g_cnt.wo, 128);
                        __syncwarp();
                    }
                    if (lane == 0) {
                        fence_proxy_async();
                        mbar_wait(bar_empty + s * 8, ((it / NSTAGE) & 1) ^ 1);
                        mbar_expect_tx(fb, 16384 + 20480);
                        tma2d(st, &mO, fb, ko * 64, f_m * 128);
                        tma2d(st + B_OFF, &mBF, fb, F_ + ko * 64, f_n * 160);
                    }
                }
            }
        } else if (c < 131) {
            G2Unit u1 = g2_unit(c, 1);
            g2_produce(u1, sbase, bar_full, bar_empty, it, 0, &mH, &mW1, lane);
        }
      } else {
        const int atid = tid - 32;
        if (main_cta) {
            for (int t = atid; t < 120; t += 96) {
                int col = (t / 40) * 640 + g1_g * 80 + (t % 40) * 2;
                const __nv_bfloat16* src = P.wqkv + (size_t)(g1_m * 40) * 1920 + col;
                float s0 = 0.f, s1 = 0.f;
#pragma unroll 8
                for (int k = 0; k < 40; k++) { uint32_t v = __ldg((const uint32_t*)(src + (size_t)k * 1920)); s0 += bf_lo(v); s1 += bf_hi(v); }
                *(float2*)&g_cs_part[g1_m][col] = make_float2(s0, s1);
            }
            if (atid < 80) {
                int kb = c >> 3, d = (c & 7) * 80 + atid;
                const __nv_bfloat16* src = P.wo + (size_t)(kb * 40) * D_ + d;
                uint32_t w[20];
#pragma unroll
                for (int k = 0; k < 20; k++) {
                    uint32_t lo = *(const uint16_t*)(src + (size_t)(2 * k) * D_), hi = *(const uint16_t*)(src + (size_t)(2 * k + 1) * D_);
                    w[k] = lo | (hi << 16);
                }
                uint4* dst = (uint4*)(g_BF + (size_t)d * KF_ + F_ + kb * 40);
#pragma unroll
                for (int k = 0; k < 5; k++) dst[k] = make_uint4(w[4 * k], w[4 * k + 1], w[4 * k + 2], w[4 * k + 3]);
            }
            fence_proxy_async();
            __threadfence();
            named_bar(2, 96);
            if (atid == 0) { red_release(&g_cnt.cs[g1_g], 1); red_release(&g_cnt.wo, 1); }
        }
        g2_finalize(u0, P.b1, atid);
        if (main_cta) {
            if (atid == 0) spin_ge(&g_cnt.cs[g1_g], 16);
            if (atid == 32) spin_ge(&g_cnt.hk[g1_m * 2], 64);
            if (atid == 64) spin_ge(&g_cnt.hk[g1_m * 2 + 1], 64);
            named_bar(2, 96);
            float* cs_s = (float*)(sgen + SM_CS);
            for (int j = atid; j < 240; j += 96) {
                int col = (j / 80) * 640 + g1_g * 80 + (j % 80);
                float s = 0.f;
#pragma unroll
                for (int m = 0; m < 16; m++) s += __ldcg(&g_cs_part[m][col]);
                cs_s[j] = s;
            }
            for (int j = atid; j < 128; j += 96) ((float2*)(sgen + SM_STATS))[j] = __ldcg(&g_stats[g1_m * 128 + j]);
            mbar_arrive(bar_aux);
            if (atid == 0) spin_ge(&g_cnt.kv[g1_g], 16);
            named_bar(2, 96);
            for (int t = atid; t < 120; t += 96) {
                int e = g1_m * 120 + t;
                float s = 0.f;
                if ((e % 24) <= 20) {
#pragma unroll
                    for (int m = 0; m < 16; m++) s += __ldcg(&g_kvpart[g1_g][m][e]);
                }
                g_kvfin[g1_g][e] = s;
            }
            __threadfence();
            named_bar(2, 96);
            if (atid == 0) { red_release(&g_cnt.kv2[g1_g], 1); spin_ge(&g_cnt.kv2[g1_g], 16); }
            named_bar(2, 96);
            uint2* kvf_s = (uint2*)(sgen + SM_KVF);
            for (int idx = atid; idx < 27 * 32; idx += 96) {
                const int p = idx >> 5, ln = idx & 31, qd = ln & 3, l4 = ln >> 2;
                const float* kvf = &g_kvfin[g1_g][0];
                int kk, ecol;
                if (p < 22) {
                    kk = p < 3 ? 0 : p < 8 ? 1 : p < 14 ? 2 : p < 19 ? 3 : 4;
                    int nt = p < 3 ? p : p < 8 ? p - 3 : p < 14 ? p - 6 : p < 19 ? p - 9 : p - 12;
                    ecol = nt * 8 + l4;
                } else { kk = p - 22; ecol = -1; }
                float bv[4];
#pragma unroll
                for (int e = 0; e < 4; e++) {
                    int d = kk * 16 + 2 * qd + (e & 1) + (e >> 1) * 8, hd = d / 20;
                    if (ecol >= 0) bv[e] = (ecol / 20 == hd) ? __ldcg(kvf + d * 24 + ecol - hd * 20) : 0.f;
                    else bv[e] = (hd == l4) ? __ldcg(kvf + d * 24 + 20) : 0.f;
                }
                kvf_s[idx] = make_uint2(pack_bf16(bv[0], bv[1]), pack_bf16(bv[2], bv[3]));
            }
            named_bar(2, 96);
            {
                const uint32_t pq_a = smem_u32(sgen + SM_PQ);
                const int aw = atid >> 5, lr = lane & 7, lm = lane >> 3, qd = lane & 3, ln4 = lane >> 2;
#pragma unroll 1
                for (int mi = aw; mi < 8; mi += 3) {
                    const int m0 = mi * 16;
                    uint32_t a[5][4];
#pragma unroll
                    for (int kk = 0; kk < 5; kk++) ldsm_x4(a[kk], pq_a + ((m0 + (lm & 1) * 8 + lr) * PQ_PITCH + kk * 16 + (lm >> 1) * 8) * 2);
                    float den[4] = {0.f, 0.f, 0.f, 0.f};
#pragma unroll
                    for (int kk = 0; kk < 5; kk++) { uint2 b = kvf_s[(22 + kk) * 32 + lane]; mma16816(den, a[kk], b.x, b.y); }
                    float dn[4][2];
#pragma unroll
                    for (int h = 0; h < 4; h++) {
                        int src = (lane & ~3) | (h >> 1);
                        float v0 = __shfl_sync(0xffffffffu, (h & 1) ? den[1] : den[0], src);
                        float v1 = __shfl_sync(0xffffffffu, (h & 1) ? den[3] : den[2], src);
                        dn[h][0] = __fdividef(1.0f, v0 + 1e-6f); dn[h][1] = __fdividef(1.0f, v1 + 1e-6f);
                    }
                    __nv_bfloat16* orow = g_o + (size_t)(g1_m * 128 + m0 + ln4) * D_ + g1_g * 80;
#pragma unroll
                    for (int nt = 0; nt < 10; nt++) {
                        float num[4] = {0.f, 0.f, 0.f, 0.f};
#pragma unroll
                        for (int kk = 0; kk < 5; kk++) {
                            const int first = kk == 0 ? 0 : kk == 1 ? 0 : kk == 2 ? 2 : kk == 3 ? 5 : 7;
                            const int cnt = kk == 0 ? 3 : kk == 1 ? 5 : kk == 2 ? 6 : kk == 3 ? 5 : 3;
                            const int off = kk == 0 ? 0 : kk == 1 ? 3 : kk == 2 ? 8 : kk == 3 ? 14 : 19;
                            if (nt >= first && nt < first + cnt) { uint2 b = kvf_s[(off + nt - first) * 32 + lane]; mma16816(num, a[kk], b.x, b.y); }
                        }
                        const int oc = nt * 8 + 2 * qd;
                        const int h0 = oc / 20;
                        float d00 = h0 == 0 ? dn[0][0] : h0 == 1 ? dn[1][0] : h0 == 2 ? dn[2][0] : dn[3][0];
                        float d01 = h0 == 0 ? dn[0][1] : h0 == 1 ? dn[1][1] : h0 == 2 ? dn[2][1] : dn[3][1];
                        *(uint32_t*)(orow + oc) = pack_bf16(num[0] * d00, num[1] * d00);
                        *(uint32_t*)(orow + 8 * D_ + oc) = pack_bf16(num[2] * d01, num[3] * d01);
                    }
                }
            }
            fence_proxy_async();
            __threadfence();
            named_bar(2, 96);
            if (atid == 0) red_release(&g_cnt.o[g1_m], 1);
        } else if (c < 131) {
            G2Unit u1 = g2_unit(c, 1);
            g2_finalize(u1, P.b1, atid);
        }
      }
    } else if (warp < 12) {
        reg_alloc<200>();
        const int ctid = tid - 128, wg = ctid >> 7, wp = (ctid >> 5) & 3;
        float acc[120];
        int it = 0;
        g2_consume(u0, sbase, bar_full, bar_empty, it, acc, wg, ctid);
        if (main_cta) {
            for (int k = 0; k < 10; k++, it++) {
                int s = it % NSTAGE;
                mbar_wait(bar_full + s * 8, (it / NSTAGE) & 1);
                mbar_wait(bar_fcp + s * 8, (k / NSTAGE) & 1);
                uint32_t st = sbase + s * STAGE_BYTES;
                uint64_t da = desc_kmajor(st + wg * 8192), db = desc_mnmajor(st + B_OFF);
                wg_fence();
#pragma unroll
                for (int kk = 0; kk < 4; kk++) wgmma_n240<0, 1>(acc, da + kk * 2, db + kk * 128, (k | kk) != 0);
                wg_commit();
                if (k > 0) { wg_wait<1>(); if ((ctid & 127) == 0) mbar_arrive(bar_empty + ((it - 1) % NSTAGE) * 8); }
            }
            wg_wait<0>();
            if ((ctid & 127) == 0) mbar_arrive(bar_empty + ((it - 1) % NSTAGE) * 8);
            mbar_wait(bar_aux, 0);
            const int sslot = it % NSTAGE;
            mbar_wait(bar_full + sslot * 8, (it / NSTAGE) & 1);
            uint8_t* stg = sgen + sslot * STAGE_BYTES;
            __nv_bfloat16* pk_s = (__nv_bfloat16*)stg;
            __nv_bfloat16* v_s = (__nv_bfloat16*)(stg + 128 * PQ_PITCH * 2);
            __nv_bfloat16* pq_s = (__nv_bfloat16*)(sgen + SM_PQ);
            const float* cs_s = (const float*)(sgen + SM_CS);
            const float2* st_s = (const float2*)(sgen + SM_STATS);
            {
                const int r0 = wg * 64 + wp * 16 + (lane >> 2), cq = 2 * (lane & 3);
                const float2 s0 = st_s[r0], s1 = st_s[r0 + 8];
#pragma unroll
                for (int j = 0; j < 30; j++) {
                    float2 cs = *(const float2*)(cs_s + 8 * j + cq);
                    float a0 = (acc[4 * j] - s0.x * cs.x) * s0.y, a1 = (acc[4 * j + 1] - s0.x * cs.y) * s0.y;
                    float a2 = (acc[4 * j + 2] - s1.x * cs.x) * s1.y, a3 = (acc[4 * j + 3] - s1.x * cs.y) * s1.y;
                    if (j < 20) {
                        a0 = (a0 > 0.f ? a0 + 1.0f : __expf(a0)) + 1e-6f;
                        a1 = (a1 > 0.f ? a1 + 1.0f : __expf(a1)) + 1e-6f;
                        a2 = (a2 > 0.f ? a2 + 1.0f : __expf(a2)) + 1e-6f;
                        a3 = (a3 > 0.f ? a3 + 1.0f : __expf(a3)) + 1e-6f;
                    }
                    __nv_bfloat16* dst = (j < 10) ? pq_s : (j < 20) ? pk_s : v_s;
                    int col = 8 * (j % 10) + cq;
                    *(uint32_t*)(dst + r0 * PQ_PITCH + col) = pack_bf16(a0, a1);
                    *(uint32_t*)(dst + (r0 + 8) * PQ_PITCH + col) = pack_bf16(a2, a3);
                }
            }
            named_bar(1, 256);
            {
                const int w8 = ctid >> 5;
                const int mt = (w8 == 0) ? 0 : (w8 <= 2) ? 1 : (w8 <= 4) ? 2 : (w8 <= 6) ? 3 : 4;
                const int n0 = (w8 == 0) ? 0 : (w8 == 1) ? 0 : (w8 == 2) ? 3 : (w8 == 3) ? 2 : (w8 == 4) ? 6 : (w8 == 5) ? 5 : (w8 == 6) ? 8 : 7;
                const int nn = (w8 == 0 || w8 == 1 || w8 == 5 || w8 == 7) ? 3 : (w8 == 3) ? 4 : 2;
                const bool doz = (w8 == 0 || w8 == 2 || w8 == 4 || w8 == 6 || w8 == 7);
                float cacc[4][4], zacc[4];
#pragma unroll
                for (int i = 0; i < 4; i++) { cacc[i][0] = cacc[i][1] = cacc[i][2] = cacc[i][3] = 0.f; zacc[i] = 0.f; }
                const uint32_t pk_a = smem_u32(pk_s), v_a = smem_u32(v_s);
                const int lr = lane & 7, lm = lane >> 3;
#pragma unroll
                for (int ks = 0; ks < 8; ks++) {
                    uint32_t a[4];
                    ldsm_x4_t(a, pk_a + ((ks * 16 + (lm >> 1) * 8 + lr) * PQ_PITCH + mt * 16 + (lm & 1) * 8) * 2);
#pragma unroll
                    for (int i = 0; i < 4; i++) {
                        if (i < nn) {
                            uint32_t b[2];
                            ldsm_x2_t(b, v_a + ((ks * 16 + (lm & 1) * 8 + lr) * PQ_PITCH + (n0 + i) * 8) * 2);
                            mma16816(cacc[i], a, b[0], b[1]);
                        }
                    }
                    if (doz) mma16816(zacc, a, 0x3F803F80u, 0x3F803F80u);
                }
                float* kvp = &g_kvpart[g1_g][g1_m][0];
                const int d0 = mt * 16 + (lane >> 2);
#pragma unroll
                for (int i = 0; i < 4; i++) {
                    if (i < nn) {
#pragma unroll
                        for (int e = 0; e < 4; e++) {
                            int d = d0 + (e >> 1) * 8, ec = (n0 + i) * 8 + 2 * (lane & 3) + (e & 1);
                            int hd = d / 20;
                            if (ec / 20 == hd) kvp[d * 24 + ec - hd * 20] = cacc[i][e];
                        }
                    }
                }
                if (doz && (lane & 3) == 0) { kvp[d0 * 24 + 20] = zacc[0]; kvp[(d0 + 8) * 24 + 20] = zacc[2]; }
            }
            __threadfence();
            named_bar(1, 256);
            if (ctid == 0) red_release(&g_cnt.kv[g1_g], 1);
            if ((ctid & 127) == 0) mbar_arrive(bar_empty + sslot * 8);
            it++;
            for (int k = 0; k < f_nk; k++, it++) {
                int s = it % NSTAGE;
                mbar_wait(bar_full + s * 8, (it / NSTAGE) & 1);
                uint32_t st = sbase + s * STAGE_BYTES;
                uint64_t db = desc_kmajor(st + B_OFF);
                wg_fence();
                if (k < f_nw2) {
                    uint64_t da = desc_mnmajor(st + wg * 8192);
#pragma unroll
                    for (int kk = 0; kk < 4; kk++) wgmma_n160<1, 0>(acc, da + kk * 128, db + kk * 2, (k | kk) != 0);
                } else {
                    uint64_t da = desc_kmajor(st + wg * 8192);
#pragma unroll
                    for (int kk = 0; kk < 4; kk++) wgmma_n160<0, 0>(acc, da + kk * 2, db + kk * 2, 1);
                }
                wg_commit();
                if (k > 0) { wg_wait<1>(); if ((ctid & 127) == 0) mbar_arrive(bar_empty + ((it - 1) % NSTAGE) * 8); }
            }
            wg_wait<0>();
            const int ftile = f_m * 4 + f_n;
            float4* fp = g_fpart + (size_t)ftile * (20 * 256) + ctid;
            const int r0 = f_m * 128 + wg * 64 + wp * 16 + (lane >> 2), cb = f_n * 160 + 2 * (lane & 3);
            if (f_hh == 1) {
                const float bb0 = __bfloat162float(P.b2[r0]), bb1 = __bfloat162float(P.b2[r0 + 8]);
#pragma unroll
                for (int q = 0; q < 20; q++) {
                    uint32_t x0 = __ldg((const uint32_t*)(P.x + (size_t)r0 * D_ + cb + 8 * q));
                    uint32_t x1 = __ldg((const uint32_t*)(P.x + (size_t)(r0 + 8) * D_ + cb + 8 * q));
                    fp[q * 256] = make_float4(acc[4 * q] + bf_lo(x0) + bb0, acc[4 * q + 1] + bf_hi(x0) + bb0,
                                              acc[4 * q + 2] + bf_lo(x1) + bb1, acc[4 * q + 3] + bf_hi(x1) + bb1);
                }
                __threadfence();
                named_bar(1, 256);
                if (ctid == 0) red_release(&g_cnt.fflag[ftile], 1);
            } else {
                if (ctid == 0) spin_ge(&g_cnt.fflag[ftile], 1);
                named_bar(1, 256);
#pragma unroll
                for (int q = 0; q < 20; q++) {
                    float4 p = __ldcg(fp + q * 256);
                    *(uint32_t*)(P.out + (size_t)r0 * D_ + cb + 8 * q) = pack_bf16(acc[4 * q] + p.x, acc[4 * q + 1] + p.y);
                    *(uint32_t*)(P.out + (size_t)(r0 + 8) * D_ + cb + 8 * q) = pack_bf16(acc[4 * q + 2] + p.z, acc[4 * q + 3] + p.w);
                }
            }
        } else if (c < 131) {
            G2Unit u1 = g2_unit(c, 1);
            g2_consume(u1, sbase, bar_full, bar_empty, it, acc, wg, ctid);
        }
    }
    __syncthreads();
    if (tid == 0) {
        __threadfence();
        unsigned prev = atomicAdd(&g_cnt.done, 1);
        if (prev == 131) {
            unsigned* p = (unsigned*)&g_cnt;
            for (int i = 0; i < (int)(sizeof(Counters) / 4); i++) p[i] = 0;
            __threadfence();
        }
    }
}

typedef CUresult (*EncodeFn)(CUtensorMap*, CUtensorMapDataType, cuuint32_t, void*, const cuuint64_t*, const cuuint64_t*, const cuuint32_t*,
                             const cuuint32_t*, CUtensorMapInterleave, CUtensorMapSwizzle, CUtensorMapL2promotion, CUtensorMapFloatOOBfill);

bool make_map(EncodeFn enc, CUtensorMap* m, const void* ptr, int rank, const cuuint64_t* dims, const cuuint64_t* strides, const cuuint32_t* box) {
    cuuint32_t es[3] = {1, 1, 1};
    return enc(m, CU_TENSOR_MAP_DATA_TYPE_BFLOAT16, rank, (void*)ptr, dims, strides, box, es, CU_TENSOR_MAP_INTERLEAVE_NONE,
               CU_TENSOR_MAP_SWIZZLE_128B, CU_TENSOR_MAP_L2_PROMOTION_L2_128B, CU_TENSOR_MAP_FLOAT_OOB_FILL_NONE) == CUDA_SUCCESS;
}

struct HostState {
    bool ready;
    const void* key[4];
    CUtensorMap mX, mH, mW1, mW2, mO, mBF;
};
HostState g_hs;

}

extern "C" void kernel_launch(void* const* d_in, const int* in_sizes, int n_in, void* d_out, int out_size) {
    const __nv_bfloat16* x = (const __nv_bfloat16*)d_in[0];
    const __nv_bfloat16* wqkv = (const __nv_bfloat16*)d_in[1];
    const __nv_bfloat16* wo = (const __nv_bfloat16*)d_in[2];
    const __nv_bfloat16* w1 = (const __nv_bfloat16*)d_in[4];
    const __nv_bfloat16* b1 = (const __nv_bfloat16*)d_in[5];
    const __nv_bfloat16* w2 = (const __nv_bfloat16*)d_in[6];
    const __nv_bfloat16* b2 = (const __nv_bfloat16*)d_in[7];
    HostState& hs = g_hs;
    if (!hs.ready || hs.key[0] != x || hs.key[1] != w1 || hs.key[2] != w2) {
        void* fn = nullptr;
        cudaDriverEntryPointQueryResult qr;
        if (cudaGetDriverEntryPoint("cuTensorMapEncodeTiled", &fn, cudaEnableDefault, &qr) != cudaSuccess || !fn) return;
        EncodeFn enc = (EncodeFn)fn;
        void *ph, *pbf, *po;
        cudaGetSymbolAddress(&ph, g_h); cudaGetSymbolAddress(&pbf, g_BF); cudaGetSymbolAddress(&po, g_o);
        {
            cuuint64_t d[2] = {640, 2048}, s[1] = {1280}; cuuint32_t b[2] = {64, 128};
            make_map(enc, &hs.mX, x, 2, d, s, b);
            make_map(enc, &hs.mO, po, 2, d, s, b);
        }
        {
            cuuint64_t d[3] = {64, 2048, 10}, s[2] = {1280, 128}; cuuint32_t b[3] = {64, 64, 2};
            make_map(enc, &hs.mH, ph, 3, d, s, b);
        }
        {
            cuuint64_t d[3] = {64, 2048, 27}, s[2] = {3456, 128}; cuuint32_t b[3] = {64, 64, 3};
            make_map(enc, &hs.mW1, w1, 3, d, s, b);
        }
        {
            cuuint64_t d[3] = {64, 1728, 32}, s[2] = {4096, 128}; cuuint32_t b[3] = {64, 64, 2};
            make_map(enc, &hs.mW2, w2, 3, d, s, b);
        }
        {
            cuuint64_t d[2] = {2368, 640}, s[1] = {4736}; cuuint32_t b[2] = {64, 160};
            make_map(enc, &hs.mBF, pbf, 2, d, s, b);
        }
        cudaFuncSetAttribute(mega_kernel, cudaFuncAttributeMaxDynamicSharedMemorySize, SMEM_ALLOC);
        hs.key[0] = x; hs.key[1] = w1; hs.key[2] = w2;
        hs.ready = true;
    }
    Params P{x, wqkv, wo, b1, b2, (__nv_bfloat16*)d_out};
    mega_kernel<<<132, 384, SMEM_ALLOC>>>(hs.mX, hs.mH, hs.mW1, hs.mW2, hs.mO, hs.mBF, P);
}
```

```cpp
#include <cuda_runtime.h>
#include <cuda.h>
#include <cuda_bf16.h>
#include <stdint.h>

namespace {

constexpr int S_ = 2048, D_ = 640, F_ = 1728, KF_ = 2368;
constexpr int NSTAGE = 4;
constexpr int STAGE_BYTES = 49152;
constexpr int B_OFF = 16384;
constexpr int PQ_PITCH = 88;
constexpr int TILE_BYTES = 128 * PQ_PITCH * 2;
constexpr int SM_X = NSTAGE * STAGE_BYTES;
constexpr int SM_KVF = SM_X + TILE_BYTES;
constexpr int SM_CS = SM_X + 32768;
constexpr int SM_STATS = SM_CS + 960;
constexpr int SM_BAR = SM_STATS + 1024;
constexpr int SMEM_ALLOC = SM_BAR + 256;

__device__ __align__(1024) __nv_bfloat16 g_h[S_ * D_];
__device__ __align__(1024) __nv_bfloat16 g_BF[D_ * KF_];
__device__ __align__(1024) __nv_bfloat16 g_o[S_ * D_];
__device__ __align__(1024) uint8_t g_wimg[8 * 10 * 32768];
__device__ float2 g_stats[S_];
__device__ float g_cs_part[16][1920];
__device__ __align__(1024) uint2 g_upart[45 * 3 * 2 * 2048];
__device__ float g_kvacc[8][1920];
__device__ __align__(1024) uint2 g_fpart[64 * 20 * 256];

struct Counters {
    unsigned hk[32];
    unsigned cs[8];
    unsigned wo;
    unsigned uflag[45];
    unsigned gflag[45];
    unsigned kv[8];
    unsigned o[16];
    unsigned fflag[64];
    unsigned done;
};
__device__ Counters g_cnt;
#define FAIL(code) __trap()
#define MBAR_LIMIT (1u << 24)
#define SPIN_LIMIT (1u << 22)
#define PROF(i)

__device__ __forceinline__ uint32_t smem_u32(const void* p) { return (uint32_t)__cvta_generic_to_shared(p); }
__device__ __forceinline__ void mbar_init(uint32_t bar, uint32_t cnt) { asm volatile("mbarrier.init.shared::cta.b64 [%0], %1;" ::"r"(bar), "r"(cnt)); }
__device__ __forceinline__ void mbar_expect_tx(uint32_t bar, uint32_t bytes) { asm volatile("mbarrier.arrive.expect_tx.shared::cta.b64 _, [%0], %1;" ::"r"(bar), "r"(bytes) : "memory"); }
__device__ __forceinline__ void mbar_arrive(uint32_t bar) { asm volatile("mbarrier.arrive.shared::cta.b64 _, [%0];" ::"r"(bar) : "memory"); }
__device__ __forceinline__ void mbar_wait(uint32_t bar, uint32_t parity) {
    uint32_t done = 0;
    for (uint32_t i = 0; i < MBAR_LIMIT; i++) {
        asm volatile("{\n.reg .pred p;\nmbarrier.try_wait.parity.shared::cta.b64 p, [%1], %2;\nselp.u32 %0, 1, 0, p;\n}" : "=r"(done) : "r"(bar), "r"(parity) : "memory");
        if (done) return;
    }
    FAIL(100 + ((bar >> 3) & 15));
}
__device__ __forceinline__ void tma2d(uint32_t dst, const CUtensorMap* m, uint32_t bar, int c0, int c1) {
    asm volatile("cp.async.bulk.tensor.2d.shared::cluster.global.mbarrier::complete_tx::bytes [%0], [%1, {%3, %4}], [%2];"
                 ::"r"(dst), "l"((uint64_t)m), "r"(bar), "r"(c0), "r"(c1) : "memory");
}
__device__ __forceinline__ void tma3d(uint32_t dst, const CUtensorMap* m, uint32_t bar, int c0, int c1, int c2) {
    asm volatile("cp.async.bulk.tensor.3d.shared::cluster.global.mbarrier::complete_tx::bytes [%0], [%1, {%3, %4, %5}], [%2];"
                 ::"r"(dst), "l"((uint64_t)m), "r"(bar), "r"(c0), "r"(c1), "r"(c2) : "memory");
}
__device__ __forceinline__ void bulk_store(void* gdst, uint32_t ssrc, uint32_t bytes) {
    asm volatile("cp.async.bulk.global.shared::cta.bulk_group [%0], [%1], %2;" ::"l"(gdst), "r"(ssrc), "r"(bytes) : "memory");
}
__device__ __forceinline__ void bulk_store_wait() {
    asm volatile("cp.async.bulk.commit_group;" ::: "memory");
    asm volatile("cp.async.bulk.wait_group 0;" ::: "memory");
}
__device__ __forceinline__ void bulk_load(uint32_t sdst, const void* gsrc, uint32_t bytes, uint32_t bar) {
    asm volatile("cp.async.bulk.shared::cluster.global.mbarrier::complete_tx::bytes [%0], [%1], %2, [%3];" ::"r"(sdst), "l"(gsrc), "r"(bytes), "r"(bar) : "memory");
}
__device__ __forceinline__ void named_arrive(int id, int n) { asm volatile("bar.arrive %0, %1;" ::"r"(id), "r"(n) : "memory"); }
__device__ __forceinline__ unsigned ld_acquire(const unsigned* p) {
    unsigned v;
    asm volatile("ld.acquire.gpu.global.u32 %0, [%1];" : "=r"(v) : "l"(p) : "memory");
    return v;
}
__device__ __forceinline__ void red_release(unsigned* p, unsigned v) {
    asm volatile("red.release.gpu.global.add.u32 [%0], %1;" ::"l"(p), "r"(v) : "memory");
}
__device__ __forceinline__ void spin_ge(const unsigned* p, unsigned target) {
    for (uint32_t i = 0; i < SPIN_LIMIT; i++) {
        if (ld_acquire(p) >= target) return;
        __nanosleep(32);
    }
    FAIL(1000 + (int)(p - (const unsigned*)&g_cnt));
}
__device__ __forceinline__ void fence_proxy_async() { asm volatile("fence.proxy.async;" ::: "memory"); }
__device__ __forceinline__ void named_bar(int id, int n) { asm volatile("bar.sync %0, %1;" ::"r"(id), "r"(n) : "memory"); }
__device__ __forceinline__ void wg_fence() { asm volatile("wgmma.fence.sync.aligned;" ::: "memory"); }
__device__ __forceinline__ void wg_commit() { asm volatile("wgmma.commit_group.sync.aligned;" ::: "memory"); }
template <int N> __device__ __forceinline__ void wg_wait() { asm volatile("wgmma.wait_group.sync.aligned %0;" ::"n"(N) : "memory"); }
template <int R> __device__ __forceinline__ void reg_alloc() { asm volatile("setmaxnreg.inc.sync.aligned.u32 %0;" ::"n"(R)); }
template <int R> __device__ __forceinline__ void reg_dealloc() { asm volatile("setmaxnreg.dec.sync.aligned.u32 %0;" ::"n"(R)); }

__device__ __forceinline__ uint64_t desc_kmajor(uint32_t addr) {
    return (uint64_t)((addr & 0x3FFFF) >> 4) | ((uint64_t)1 << 16) | ((uint64_t)64 << 32) | ((uint64_t)1 << 62);
}
__device__ __forceinline__ uint64_t desc_mnmajor(uint32_t addr) {
    return (uint64_t)((addr & 0x3FFFF) >> 4) | ((uint64_t)512 << 16) | ((uint64_t)64 << 32) | ((uint64_t)1 << 62);
}
__device__ __forceinline__ uint32_t pack_bf16(float a, float b) {
    uint32_t r;
    asm("cvt.rn.bf16x2.f32 %0, %1, %2;" : "=r"(r) : "f"(b), "f"(a));
    return r;
}
__device__ __forceinline__ float bf_lo(uint32_t v) { return __uint_as_float(v << 16); }
__device__ __forceinline__ float bf_hi(uint32_t v) { return __uint_as_float(v & 0xFFFF0000u); }
__device__ __forceinline__ float warp_sum(float v) {
#pragma unroll
    for (int o = 16; o > 0; o >>= 1) v += __shfl_xor_sync(0xffffffffu, v, o);
    return v;
}
__device__ __forceinline__ void ldsm_x4(uint32_t (&r)[4], uint32_t addr) {
    asm volatile("ldmatrix.sync.aligned.m8n8.x4.shared.b16 {%0,%1,%2,%3}, [%4];" : "=r"(r[0]), "=r"(r[1]), "=r"(r[2]), "=r"(r[3]) : "r"(addr) : "memory");
}
__device__ __forceinline__ void ldsm_x4_t(uint32_t (&r)[4], uint32_t addr) {
    asm volatile("ldmatrix.sync.aligned.m8n8.x4.trans.shared.b16 {%0,%1,%2,%3}, [%4];" : "=r"(r[0]), "=r"(r[1]), "=r"(r[2]), "=r"(r[3]) : "r"(addr) : "memory");
}
__device__ __forceinline__ void ldsm_x2_t(uint32_t (&r)[2], uint32_t addr) {
    asm volatile("ldmatrix.sync.aligned.m8n8.x2.trans.shared.b16 {%0,%1}, [%2];" : "=r"(r[0]), "=r"(r[1]) : "r"(addr) : "memory");
}
__device__ __forceinline__ void mma16816(float (&c)[4], const uint32_t (&a)[4], uint32_t b0, uint32_t b1) {
    asm volatile("mma.sync.aligned.m16n8k16.row.col.f32.bf16.bf16.f32 {%0,%1,%2,%3}, {%4,%5,%6,%7}, {%8,%9}, {%0,%1,%2,%3};"
                 : "+f"(c[0]), "+f"(c[1]), "+f"(c[2]), "+f"(c[3]) : "r"(a[0]), "r"(a[1]), "r"(a[2]), "r"(a[3]), "r"(b0), "r"(b1));
}
__device__ __forceinline__ float gelu_tanh(float u) {
    float z = 1.5957691216057308f * (u + 0.044715f * u * u * u);
    return __fdividef(u, 1.0f + __expf(-z));
}

template<int TA, int TB>
__device__ __forceinline__ void wgmma_n160(float (&d)[120], uint64_t da, uint64_t db, int scale_d) {
    asm volatile("{\n.reg .pred p;\nsetp.ne.b32 p, %82, 0;\n"
        "wgmma.mma_async.sync.aligned.m64n160k16.f32.bf16.bf16 "
        "{%0, %1, %2, %3, %4, %5, %6, %7, %8, %9, %10, %11, %12, %13, %14, %15, "
        "%16, %17, %18, %19, %20, %21, %22, %23, %24, %25, %26, %27, %28, %29, %30, %31, "
        "%32, %33, %34, %35, %36, %37, %38, %39, %40, %41, %42, %43, %44, %45, %46, %47, "
        "%48, %49, %50, %51, %52, %53, %54, %55, %56, %57, %58, %59, %60, %61, %62, %63, "
        "%64, %65, %66, %67, %68, %69, %70, %71, %72, %73, %74, %75, %76, %77, %78, %79}, "
        "%80, %81, p, 1, 1, %83, %84;\n}\n"
        : "+f"(d[0]), "+f"(d[1]), "+f"(d[2]), "+f"(d[3]), "+f"(d[4]), "+f"(d[5]), "+f"(d[6]), "+f"(d[7]),
          "+f"(d[8]), "+f"(d[9]), "+f"(d[10]), "+f"(d[11]), "+f"(d[12]), "+f"(d[13]), "+f"(d[14]), "+f"(d[15]),
          "+f"(d[16]), "+f"(d[17]), "+f"(d[18]), "+f"(d[19]), "+f"(d[20]), "+f"(d[21]), "+f"(d[22]), "+f"(d[23]),
          "+f"(d[24]), "+f"(d[25]), "+f"(d[26]), "+f"(d[27]), "+f"(d[28]), "+f"(d[29]), "+f"(d[30]), "+f"(d[31]),
          "+f"(d[32]), "+f"(d[33]), "+f"(d[34]), "+f"(d[35]), "+f"(d[36]), "+f"(d[37]), "+f"(d[38]), "+f"(d[39]),
          "+f"(d[40]), "+f"(d[41]), "+f"(d[42]), "+f"(d[43]), "+f"(d[44]), "+f"(d[45]), "+f"(d[46]), "+f"(d[47]),
          "+f"(d[48]), "+f"(d[49]), "+f"(d[50]), "+f"(d[51]), "+f"(d[52]), "+f"(d[53]), "+f"(d[54]), "+f"(d[55]),
          "+f"(d[56]), "+f"(d[57]), "+f"(d[58]), "+f"(d[59]), "+f"(d[60]), "+f"(d[61]), "+f"(d[62]), "+f"(d[63]),
          "+f"(d[64]), "+f"(d[65]), "+f"(d[66]), "+f"(d[67]), "+f"(d[68]), "+f"(d[69]), "+f"(d[70]), "+f"(d[71]),
          "+f"(d[72]), "+f"(d[73]), "+f"(d[74]), "+f"(d[75]), "+f"(d[76]), "+f"(d[77]), "+f"(d[78]), "+f"(d[79])
        : "l"(da), "l"(db), "r"(scale_d), "n"(TA), "n"(TB));
}

template<int TA, int TB>
__device__ __forceinline__ void wgmma_n192(float (&d)[120], uint64_t da, uint64_t db, int scale_d) {
    asm volatile("{\n.reg .pred p;\nsetp.ne.b32 p, %98, 0;\n"
        "wgmma.mma_async.sync.aligned.m64n192k16.f32.bf16.bf16 "
        "{%0, %1, %2, %3, %4, %5, %6, %7, %8, %9, %10, %11, %12, %13, %14, %15, "
        "%16, %17, %18, %19, %20, %21, %22, %23, %24, %25, %26, %27, %28, %29, %30, %31, "
        "%32, %33, %34, %35, %36, %37, %38, %39, %40, %41, %42, %43, %44, %45, %46, %47, "
        "%48, %49, %50, %51, %52, %53, %54, %55, %56, %57, %58, %59, %60, %61, %62, %63, "
        "%64, %65, %66, %67, %68, %69, %70, %71, %72, %73, %74, %75, %76, %77, %78, %79, "
        "%80, %81, %82, %83, %84, %85, %86, %87, %88, %89, %90, %91, %92, %93, %94, %95}, "
        "%96, %97, p, 1, 1, %99, %100;\n}\n"
        : "+f"(d[0]), "+f"(d[1]), "+f"(d[2]), "+f"(d[3]), "+f"(d[4]), "+f"(d[5]), "+f"(d[6]), "+f"(d[7]),
          "+f"(d[8]), "+f"(d[9]), "+f"(d[10]), "+f"(d[11]), "+f"(d[12]), "+f"(d[13]), "+f"(d[14]), "+f"(d[15]),
          "+f"(d[16]), "+f"(d[17]), "+f"(d[18]), "+f"(d[19]), "+f"(d[20]), "+f"(d[21]), "+f"(d[22]), "+f"(d[23]),
          "+f"(d[24]), "+f"(d[25]), "+f"(d[26]), "+f"(d[27]), "+f"(d[28]), "+f"(d[29]), "+f"(d[30]), "+f"(d[31]),
          "+f"(d[32]), "+f"(d[33]), "+f"(d[34]), "+f"(d[35]), "+f"(d[36]), "+f"(d[37]), "+f"(d[38]), "+f"(d[39]),
          "+f"(d[40]), "+f"(d[41]), "+f"(d[42]), "+f"(d[43]), "+f"(d[44]), "+f"(d[45]), "+f"(d[46]), "+f"(d[47]),
          "+f"(d[48]), "+f"(d[49]), "+f"(d[50]), "+f"(d[51]), "+f"(d[52]), "+f"(d[53]), "+f"(d[54]), "+f"(d[55]),
          "+f"(d[56]), "+f"(d[57]), "+f"(d[58]), "+f"(d[59]), "+f"(d[60]), "+f"(d[61]), "+f"(d[62]), "+f"(d[63]),
          "+f"(d[64]), "+f"(d[65]), "+f"(d[66]), "+f"(d[67]), "+f"(d[68]), "+f"(d[69]), "+f"(d[70]), "+f"(d[71]),
          "+f"(d[72]), "+f"(d[73]), "+f"(d[74]), "+f"(d[75]), "+f"(d[76]), "+f"(d[77]), "+f"(d[78]), "+f"(d[79]),
          "+f"(d[80]), "+f"(d[81]), "+f"(d[82]), "+f"(d[83]), "+f"(d[84]), "+f"(d[85]), "+f"(d[86]), "+f"(d[87]),
          "+f"(d[88]), "+f"(d[89]), "+f"(d[90]), "+f"(d[91]), "+f"(d[92]), "+f"(d[93]), "+f"(d[94]), "+f"(d[95])
        : "l"(da), "l"(db), "r"(scale_d), "n"(TA), "n"(TB));
}

template<int TA, int TB>
__device__ __forceinline__ void wgmma_n240(float (&d)[120], uint64_t da, uint64_t db, int scale_d) {
    asm volatile("{\n.reg .pred p;\nsetp.ne.b32 p, %122, 0;\n"
        "wgmma.mma_async.sync.aligned.m64n240k16.f32.bf16.bf16 "
        "{%0, %1, %2, %3, %4, %5, %6, %7, %8, %9, %10, %11, %12, %13, %14, %15, "
        "%16, %17, %18, %19, %20, %21, %22, %23, %24, %25, %26, %27, %28, %29, %30, %31, "
        "%32, %33, %34, %35, %36, %37, %38, %39, %40, %41, %42, %43, %44, %45, %46, %47, "
        "%48, %49, %50, %51, %52, %53, %54, %55, %56, %57, %58, %59, %60, %61, %62, %63, "
        "%64, %65, %66, %67, %68, %69, %70, %71, %72, %73, %74, %75, %76, %77, %78, %79, "
        "%80, %81, %82, %83, %84, %85, %86, %87, %88, %89, %90, %91, %92, %93, %94, %95, "
        "%96, %97, %98, %99, %100, %101, %102, %103, %104, %105, %106, %107, %108, %109, %110, %111, "
        "%112, %113, %114, %115, %116, %117, %118, %119}, "
        "%120, %121, p, 1, 1, %123, %124;\n}\n"
        : "+f"(d[0]), "+f"(d[1]), "+f"(d[2]), "+f"(d[3]), "+f"(d[4]), "+f"(d[5]), "+f"(d[6]), "+f"(d[7]),
          "+f"(d[8]), "+f"(d[9]), "+f"(d[10]), "+f"(d[11]), "+f"(d[12]), "+f"(d[13]), "+f"(d[14]), "+f"(d[15]),
          "+f"(d[16]), "+f"(d[17]), "+f"(d[18]), "+f"(d[19]), "+f"(d[20]), "+f"(d[21]), "+f"(d[22]), "+f"(d[23]),
          "+f"(d[24]), "+f"(d[25]), "+f"(d[26]), "+f"(d[27]), "+f"(d[28]), "+f"(d[29]), "+f"(d[30]), "+f"(d[31]),
          "+f"(d[32]), "+f"(d[33]), "+f"(d[34]), "+f"(d[35]), "+f"(d[36]), "+f"(d[37]), "+f"(d[38]), "+f"(d[39]),
          "+f"(d[40]), "+f"(d[41]), "+f"(d[42]), "+f"(d[43]), "+f"(d[44]), "+f"(d[45]), "+f"(d[46]), "+f"(d[47]),
          "+f"(d[48]), "+f"(d[49]), "+f"(d[50]), "+f"(d[51]), "+f"(d[52]), "+f"(d[53]), "+f"(d[54]), "+f"(d[55]),
          "+f"(d[56]), "+f"(d[57]), "+f"(d[58]), "+f"(d[59]), "+f"(d[60]), "+f"(d[61]), "+f"(d[62]), "+f"(d[63]),
          "+f"(d[64]), "+f"(d[65]), "+f"(d[66]), "+f"(d[67]), "+f"(d[68]), "+f"(d[69]), "+f"(d[70]), "+f"(d[71]),
          "+f"(d[72]), "+f"(d[73]), "+f"(d[74]), "+f"(d[75]), "+f"(d[76]), "+f"(d[77]), "+f"(d[78]), "+f"(d[79]),
          "+f"(d[80]), "+f"(d[81]), "+f"(d[82]), "+f"(d[83]), "+f"(d[84]), "+f"(d[85]), "+f"(d[86]), "+f"(d[87]),
          "+f"(d[88]), "+f"(d[89]), "+f"(d[90]), "+f"(d[91]), "+f"(d[92]), "+f"(d[93]), "+f"(d[94]), "+f"(d[95]),
          "+f"(d[96]), "+f"(d[97]), "+f"(d[98]), "+f"(d[99]), "+f"(d[100]), "+f"(d[101]), "+f"(d[102]), "+f"(d[103]),
          "+f"(d[104]), "+f"(d[105]), "+f"(d[106]), "+f"(d[107]), "+f"(d[108]), "+f"(d[109]), "+f"(d[110]), "+f"(d[111]),
          "+f"(d[112]), "+f"(d[113]), "+f"(d[114]), "+f"(d[115]), "+f"(d[116]), "+f"(d[117]), "+f"(d[118]), "+f"(d[119])
        : "l"(da), "l"(db), "r"(scale_d), "n"(TA), "n"(TB));
}

struct Params {
    const __nv_bfloat16* x;
    const __nv_bfloat16* wqkv;
    const __nv_bfloat16* wo;
    const __nv_bfloat16* b1;
    const __nv_bfloat16* b2;
    __nv_bfloat16* out;
};

struct G2Unit { int dt, ft, ks, kb0, nk, tile; };
__device__ __forceinline__ G2Unit g2_unit(int c, int round) {
    G2Unit u;
    if (round == 0) {
        int p = c >> 1, r = c & 1;
        if (p < 54) { int dp = p / 27, rem = p % 27; u.ft = rem / 3; u.ks = rem % 3; u.dt = 2 * dp + r; }
        else { int q = p - 54; u.ks = q % 3; u.dt = 4; u.ft = 2 * (q / 3) + r; }
    } else { u.dt = 4; u.ft = 8; u.ks = c - 128; }
    u.kb0 = u.ks * 11; u.nk = (u.ks == 2) ? 10 : 11; u.tile = u.dt * 9 + u.ft;
    return u;
}

constexpr int F_L_W2 = 13, F_L = F_L_W2 + 10, F_S = 27 - F_L_W2;
constexpr int K_FIN = 6;
constexpr int K_O = 9;

__device__ __forceinline__ void g2_produce(const G2Unit& u, uint32_t sbase, uint32_t bar_full, uint32_t bar_empty, int& it, int pre,
                                           const CUtensorMap* mH, const CUtensorMap* mW1, int lane) {
    if (lane < u.nk) spin_ge(&g_cnt.hk[u.kb0 + lane], 64);
    __syncwarp();
    if (lane == 0 && it == 0) PROF(24);
    if (lane == 0) {
        fence_proxy_async();
        for (int k = 0; k < u.nk; k++, it++) {
            int s = it % NSTAGE;
            uint32_t st = sbase + s * STAGE_BYTES, fb = bar_full + s * 8;
            if (k >= pre) {
                mbar_wait(bar_empty + s * 8, ((it / NSTAGE) & 1) ^ 1);
                mbar_expect_tx(fb, 16384 + 24576);
                tma3d(st + B_OFF, mW1, fb, 0, (u.kb0 + k) * 64, u.ft * 3);
            }
            tma3d(st, mH, fb, 0, (u.kb0 + k) * 64, u.dt * 2);
        }
    } else {
        it += u.nk;
    }
    __syncwarp();
}

__device__ __forceinline__ void g2_consume(const G2Unit& u, uint32_t sbase, uint8_t* sgen, uint32_t bar_full, uint32_t bar_empty, int& it,
                                           float (&acc)[120], float (&keep)[32], int wg, int ctid) {
    for (int k = 0; k < u.nk; k++, it++) {
        int s = it % NSTAGE;
        mbar_wait(bar_full + s * 8, (it / NSTAGE) & 1);
        if (it == 0 && ctid == 0) PROF(2);
        uint32_t st = sbase + s * STAGE_BYTES;
        uint64_t da = desc_mnmajor(st + wg * 8192), db = desc_mnmajor(st + B_OFF);
        wg_fence();
#pragma unroll
        for (int kk = 0; kk < 4; kk++) wgmma_n192<1, 1>(acc, da + kk * 128, db + kk * 128, (k | kk) != 0);
        wg_commit();
        if (k > 0) { wg_wait<1>(); if ((ctid & 127) == 0) mbar_arrive(bar_empty + ((it - 1) % NSTAGE) * 8); }
    }
    wg_wait<0>();
    if ((ctid & 127) == 0) mbar_arrive(bar_empty + ((it - 1) % NSTAGE) * 8);
    if (it <= 11 && ctid == 0) PROF(3);
    uint2* rem = (uint2*)(sgen + SM_X) + ctid;
#pragma unroll
    for (int t3 = 0; t3 < 3; t3++) {
        if (t3 == u.ks) {
#pragma unroll
            for (int j = 0; j < 32; j++) keep[j] = acc[32 * t3 + j];
        } else {
            uint2* r = rem + ((t3 > u.ks) ? t3 - 1 : t3) * 2048;
#pragma unroll
            for (int q = 0; q < 8; q++) { const int j = 4 * (8 * t3 + q); r[q * 256] = make_uint2(pack_bf16(acc[j], acc[j + 1]), pack_bf16(acc[j + 2], acc[j + 3])); }
        }
    }
    asm volatile("fence.proxy.async.shared::cta;" ::: "memory");
    named_arrive(3, 352);
    if (it <= 11 && ctid == 0) PROF(4);
}

__device__ __forceinline__ void g2_exchange(const G2Unit& u, uint32_t sbase, uint32_t bar_x, int atid) {
    named_bar(3, 352);
    if (atid == 0) {
#pragma unroll
        for (int i = 0; i < 2; i++) {
            int t3 = i + (i >= u.ks);
            int slot = (u.ks > t3) ? u.ks - 1 : u.ks;
            bulk_store(g_upart + (size_t)((u.tile * 3 + t3) * 2 + slot) * 2048, sbase + SM_X + i * 16384, 16384);
        }
        bulk_store_wait();
        fence_proxy_async();
        red_release(&g_cnt.uflag[u.tile], 1);
        spin_ge(&g_cnt.uflag[u.tile], 3);
        fence_proxy_async();
        mbar_expect_tx(bar_x, 32768);
        bulk_load(sbase + SM_X, g_upart + (size_t)((u.tile * 3 + u.ks) * 2) * 2048, 32768, bar_x);
    }
}

__device__ __forceinline__ void g2_finalize(const G2Unit& u, const __nv_bfloat16* b1, uint8_t* sgen, uint32_t bar_x, uint32_t xpar,
                                            const float (&keep)[32], int wg, int wp, int lane, int ctid) {
    const int row = u.dt * 128 + wg * 64 + wp * 16 + (lane >> 2);
    const int colb = u.ft * 192 + u.ks * 64 + 2 * (lane & 3);
    uint32_t bb[8];
#pragma unroll
    for (int q = 0; q < 8; q++) bb[q] = __ldg((const uint32_t*)(b1 + colb + 8 * q));
    mbar_wait(bar_x, xpar);
    const uint2* rem = (const uint2*)(sgen + SM_X) + ctid;
    __nv_bfloat16* g0 = g_BF + (size_t)row * KF_ + colb;
#pragma unroll
    for (int q = 0; q < 8; q++) {
        uint2 b = rem[q * 256], c = rem[2048 + q * 256];
        float bl = bf_lo(bb[q]), bh = bf_hi(bb[q]);
        float u0 = gelu_tanh(keep[4 * q] + bf_lo(b.x) + bf_lo(c.x) + bl), u1 = gelu_tanh(keep[4 * q + 1] + bf_hi(b.x) + bf_hi(c.x) + bh);
        float u2 = gelu_tanh(keep[4 * q + 2] + bf_lo(b.y) + bf_lo(c.y) + bl), u3 = gelu_tanh(keep[4 * q + 3] + bf_hi(b.y) + bf_hi(c.y) + bh);
        *(uint32_t*)(g0 + 8 * q) = pack_bf16(u0, u1);
        *(uint32_t*)(g0 + 8 * KF_ + 8 * q) = pack_bf16(u2, u3);
    }
    fence_proxy_async();
    named_arrive(4, 352);
}

__global__ void __cluster_dims__(2, 1, 1) __launch_bounds__(384, 1)
mega_kernel(const __grid_constant__ CUtensorMap mX, const __grid_constant__ CUtensorMap mH, const __grid_constant__ CUtensorMap mW1,
            const __grid_constant__ CUtensorMap mW2, const __grid_constant__ CUtensorMap mO, const __grid_constant__ CUtensorMap mBF,
            const Params P) {
    extern __shared__ __align__(1024) uint8_t smem_raw[];
    const uint32_t sbase = smem_u32(smem_raw);
    uint8_t* sgen = smem_raw;
    const uint32_t bar_full = sbase + SM_BAR, bar_empty = bar_full + 32, bar_aux = bar_full + 64, bar_x = bar_full + 72, bar_kv = bar_full + 80, bar_kvl = bar_full + 88;
    const int tid = threadIdx.x, warp = tid >> 5, lane = tid & 31;
    const int c = blockIdx.x;
    const bool main_cta = c < 128;
    if (tid == 0) PROF(0);

    const int hl = lane & 15;
    const int ln_row = c * 16 + (warp - 4) * 2 + (lane >> 4);
    uint4 xv[5];
    if (main_cta && warp >= 4) {
        const uint4* xr = (const uint4*)(P.x + (size_t)ln_row * D_);
#pragma unroll
        for (int i = 0; i < 5; i++) xv[i] = __ldg(xr + hl + 16 * i);
    }
    const G2Unit u0 = g2_unit(c, 0);
    if (tid == 0) {
        if (sbase & 1023) __trap();
        for (int i = 0; i < NSTAGE; i++) { mbar_init(bar_full + i * 8, 1); mbar_init(bar_empty + i * 8, 2); }
        mbar_init(bar_aux, 96);
        mbar_init(bar_x, 1);
        mbar_init(bar_kv, 96);
        mbar_init(bar_kvl, 1);
        asm volatile("fence.mbarrier_init.release.cluster;" ::: "memory");
        for (int k = 0; k < NSTAGE; k++) {
            uint32_t fb = bar_full + k * 8;
            mbar_expect_tx(fb, 16384 + 24576);
            tma3d(sbase + k * STAGE_BYTES + B_OFF, &mW1, fb, 0, (u0.kb0 + k) * 64, u0.ft * 3);
        }
    }
    if (main_cta && warp >= 4) {
        float f[40];
#pragma unroll
        for (int i = 0; i < 5; i++) {
            uint4 v = xv[i];
            f[8 * i] = bf_lo(v.x); f[8 * i + 1] = bf_hi(v.x); f[8 * i + 2] = bf_lo(v.y); f[8 * i + 3] = bf_hi(v.y);
            f[8 * i + 4] = bf_lo(v.z); f[8 * i + 5] = bf_hi(v.z); f[8 * i + 6] = bf_lo(v.w); f[8 * i + 7] = bf_hi(v.w);
        }
        auto hsum = [](float v) {
#pragma unroll
            for (int o = 8; o > 0; o >>= 1) v += __shfl_xor_sync(0xffffffffu, v, o);
            return v;
        };
        float s = 0.f;
#pragma unroll
        for (int i = 0; i < 40; i++) s += f[i];
        const float mean = hsum(s) * (1.0f / D_);
        float q = 0.f;
#pragma unroll
        for (int i = 0; i < 40; i++) { f[i] -= mean; q += f[i] * f[i]; }
        const float rstd = rsqrtf(hsum(q) * (1.0f / D_) + 1e-5f);
        s = 0.f;
#pragma unroll
        for (int i = 0; i < 40; i += 2) {
            uint32_t p = pack_bf16(f[i] * rstd, f[i + 1] * rstd);
            f[i] = bf_lo(p); f[i + 1] = bf_hi(p);
            s += f[i] + f[i + 1];
        }
        const float mean2 = hsum(s) * (1.0f / D_);
        q = 0.f;
#pragma unroll
        for (int i = 0; i < 40; i++) { f[i] -= mean2; q += f[i] * f[i]; }
        const float rstd2 = rsqrtf(hsum(q) * (1.0f / D_) + 1e-5f);
        uint4* hr = (uint4*)(g_h + (size_t)ln_row * D_);
#pragma unroll
        for (int i = 0; i < 5; i++) {
            uint4 v;
            v.x = pack_bf16(f[8 * i] * rstd2, f[8 * i + 1] * rstd2); v.y = pack_bf16(f[8 * i + 2] * rstd2, f[8 * i + 3] * rstd2);
            v.z = pack_bf16(f[8 * i + 4] * rstd2, f[8 * i + 5] * rstd2); v.w = pack_bf16(f[8 * i + 6] * rstd2, f[8 * i + 7] * rstd2);
            hr[hl + 16 * i] = v;
        }
        if (hl == 0) g_stats[ln_row] = make_float2(mean, rstd);
        fence_proxy_async();
        __syncwarp();
        if (lane == 0) red_release(&g_cnt.hk[c >> 2], 2);
    }
    __syncthreads();

    const int pr = c >> 1, rk = c & 1;
    const int g1_g = pr & 7, g1_m = 2 * ((pr >> 3) & 7) + rk;
    const int f_m = 2 * (pr & 7) + rk, f_n = (pr >> 3) & 3, f_hh = (pr >> 5) & 1;
    const int f_nw2 = f_hh ? F_S : F_L_W2, f_kb0 = f_hh ? F_L_W2 : 0, f_nk = f_hh ? F_S : F_L;

    if (warp < 4) {
      reg_dealloc<96>();
      if (warp == 0) {
        int it = 0;
        g2_produce(u0, sbase, bar_full, bar_empty, it, NSTAGE, &mH, &mW1, lane);
        if (main_cta) {
            if (lane == 0) {
                spin_ge(&g_cnt.cs[g1_g], 16);
                fence_proxy_async();
                int itl = it;
                for (int k = 0; k < 10; k++, itl++) {
                    int s = itl % NSTAGE;
                    uint32_t st = sbase + s * STAGE_BYTES, fb = bar_full + s * 8;
                    mbar_wait(bar_empty + s * 8, ((itl / NSTAGE) & 1) ^ 1);
                    mbar_expect_tx(fb, 16384 + 32768);
                    tma2d(st, &mX, fb, k * 64, g1_m * 128);
                    bulk_load(st + B_OFF, g_wimg + (size_t)(g1_g * 10 + k) * 32768, 32768, fb);
                }
                PROF(25);
            }
            it += 10;
            if (lane == 0) {
                int s = it % NSTAGE;
                mbar_wait(bar_empty + s * 8, ((it / NSTAGE) & 1) ^ 1);
                mbar_arrive(bar_full + s * 8);
            }
            it++;
            __syncwarp();
            const int dt0 = (f_n * 160) >> 7, dt1 = (f_n * 160 + 159) >> 7;
            {
                const int ft_lo = f_kb0 / 3, ft_hi = min((f_kb0 + f_nw2 - 1) / 3, 7);
                const int ft = ft_lo + (lane >> 1);
                if (ft <= ft_hi) spin_ge(&g_cnt.gflag[((lane & 1) ? dt1 : dt0) * 9 + ft], 3);
                __syncwarp();
                if (lane == 0) { fence_proxy_async(); PROF(26); }
            }
            for (int k = 0; k < f_nk; k++, it++) {
                int s = it % NSTAGE;
                uint32_t st = sbase + s * STAGE_BYTES, fb = bar_full + s * 8;
                if (k < f_nw2) {
                    int kb = f_kb0 + k;
                    if (kb == 24) {
                        if (lane < 2) spin_ge(&g_cnt.gflag[(lane ? dt1 : dt0) * 9 + 8], 3);
                        __syncwarp();
                        if (lane == 0) fence_proxy_async();
                    }
                    if (lane == 0) {
                        mbar_wait(bar_empty + s * 8, ((it / NSTAGE) & 1) ^ 1);
                        mbar_expect_tx(fb, 16384 + 20480);
                        tma3d(st, &mW2, fb, 0, kb * 64, f_m * 2);
                        tma2d(st + B_OFF, &mBF, fb, kb * 64, f_n * 160);
                    }
                } else {
                    int ko = k - f_nw2;
                    if (ko == 0) {
                        if (lane == 0) spin_ge(&g_cnt.o[f_m], 8);
                        if (lane == 1) spin_ge(&g_cnt.wo, 128);
                        __syncwarp();
                        if (lane == 0) { fence_proxy_async(); PROF(27); }
                    }
                    if (lane == 0) {
                        mbar_wait(bar_empty + s * 8, ((it / NSTAGE) & 1) ^ 1);
                        mbar_expect_tx(fb, 16384 + 20480);
                        tma2d(st, &mO, fb, ko * 64, f_m * 128);
                        tma2d(st + B_OFF, &mBF, fb, F_ + ko * 64, f_n * 160);
                    }
                }
            }
            if (f_hh == 0 && lane == 0) {
                int s = it % NSTAGE;
                mbar_wait(bar_empty + s * 8, ((it / NSTAGE) & 1) ^ 1);
                spin_ge(&g_cnt.fflag[f_m * 4 + f_n], 1);
                fence_proxy_async();
                mbar_expect_tx(bar_full + s * 8, 40960);
                bulk_load(sbase + s * STAGE_BYTES, g_fpart + (size_t)(f_m * 4 + f_n) * (20 * 256), 40960, bar_full + s * 8);
            }
        } else if (c < 131) {
            G2Unit u1 = g2_unit(c, 1);
            g2_produce(u1, sbase, bar_full, bar_empty, it, 0, &mH, &mW1, lane);
        }
      } else {
        const int atid = tid - 32;
        if (main_cta) {
            float* tmp = (float*)(sgen + SM_CS);
            for (int j = atid; j < 240; j += 96) tmp[j] = 0.f;
            named_bar(2, 96);
            if (atid < 90) {
                const int cidx = atid % 30, rg = atid / 30;
                const __nv_bfloat16* src = P.wqkv + (size_t)(g1_m * 40) * 1920 + (cidx / 10) * 640 + g1_g * 80 + (cidx % 10) * 8;
                uint4 v[14];
#pragma unroll
                for (int i = 0; i < 14; i++) { int r = rg + 3 * i; if (r < 40) v[i] = __ldg((const uint4*)(src + (size_t)r * 1920)); }
                float cs[8] = {0.f, 0.f, 0.f, 0.f, 0.f, 0.f, 0.f, 0.f};
#pragma unroll
                for (int i = 0; i < 14; i++) {
                    int r = rg + 3 * i;
                    if (r < 40) {
                        int kg = g1_m * 40 + r, kb = kg >> 6, rr = kg & 63;
                        *(uint4*)(g_wimg + (size_t)(g1_g * 10 + kb) * 32768 + (cidx >> 3) * 8192 + rr * 128 + (((cidx & 7) ^ (rr & 7)) << 4)) = v[i];
                        cs[0] += bf_lo(v[i].x); cs[1] += bf_hi(v[i].x); cs[2] += bf_lo(v[i].y); cs[3] += bf_hi(v[i].y);
                        cs[4] += bf_lo(v[i].z); cs[5] += bf_hi(v[i].z); cs[6] += bf_lo(v[i].w); cs[7] += bf_hi(v[i].w);
                    }
                }
#pragma unroll
                for (int e = 0; e < 8; e++) atomicAdd(&tmp[cidx * 8 + e], cs[e]);
            }
            if (atid < 80) {
                int kb = c >> 3, d = (c & 7) * 80 + atid;
                const __nv_bfloat16* src = P.wo + (size_t)(kb * 40) * D_ + d;
                uint32_t w[20];
#pragma unroll
                for (int k = 0; k < 20; k++) {
                    uint32_t lo = *(const uint16_t*)(src + (size_t)(2 * k) * D_), hi = *(const uint16_t*)(src + (size_t)(2 * k + 1) * D_);
                    w[k] = lo | (hi << 16);
                }
                uint4* dst = (uint4*)(g_BF + (size_t)d * KF_ + F_ + kb * 40);
#pragma unroll
                for (int k = 0; k < 5; k++) dst[k] = make_uint4(w[4 * k], w[4 * k + 1], w[4 * k + 2], w[4 * k + 3]);
            }
            named_bar(2, 96);
            for (int j = atid; j < 240; j += 96) g_cs_part[g1_m][(j / 80) * 640 + g1_g * 80 + (j % 80)] = tmp[j];
            fence_proxy_async();
            named_bar(2, 96);
            if (atid == 0) { red_release(&g_cnt.cs[g1_g], 1); red_release(&g_cnt.wo, 1); PROF(16); }
            if (atid == 0) spin_ge(&g_cnt.cs[g1_g], 16);
            if (atid == 32) spin_ge(&g_cnt.hk[g1_m * 2], 64);
            if (atid == 64) spin_ge(&g_cnt.hk[g1_m * 2 + 1], 64);
            named_bar(2, 96);
            float* cs_s = (float*)(sgen + SM_CS);
            {
                float part[3][16];
#pragma unroll
                for (int i = 0; i < 3; i++) {
                    int j = atid + 96 * i;
                    if (j < 240) {
                        int col = (j / 80) * 640 + g1_g * 80 + (j % 80);
#pragma unroll
                        for (int m = 0; m < 16; m++) part[i][m] = __ldcg(&g_cs_part[m][col]);
                    }
                }
                float2 st0 = __ldcg(&g_stats[g1_m * 128 + atid]);
                float2 st1 = make_float2(0.f, 0.f);
                if (atid < 32) st1 = __ldcg(&g_stats[g1_m * 128 + 96 + atid]);
#pragma unroll
                for (int i = 0; i < 3; i++) {
                    int j = atid + 96 * i;
                    if (j < 240) {
                        float s = 0.f;
#pragma unroll
                        for (int m = 0; m < 16; m++) s += part[i][m];
                        cs_s[j] = s;
                    }
                }
                ((float2*)(sgen + SM_STATS))[atid] = st0;
                if (atid < 32) ((float2*)(sgen + SM_STATS))[96 + atid] = st1;
            }
            mbar_arrive(bar_aux);
            if (atid == 0) PROF(17);
        }
        g2_exchange(u0, sbase, bar_x, atid);
        if (atid == 0) PROF(18);
        named_bar(4, 352);
        if (atid == 0) { red_release(&g_cnt.gflag[u0.tile], 1); PROF(19); }
        if (main_cta) {
            named_bar(5, 352);
            if (atid == 0) {
                red_release(&g_cnt.kv[g1_g], 1);
                spin_ge(&g_cnt.kv[g1_g], 16);
                fence_proxy_async();
                mbar_expect_tx(bar_kvl, 7680);
                bulk_load(sbase + SM_CS - 7680, &g_kvacc[g1_g][0], 7680, bar_kvl);
                PROF(20);
            }
            mbar_wait(bar_kvl, 0);
            uint2 fr[9];
            const float* kvf = (const float*)(sgen + SM_CS - 7680);
#pragma unroll
            for (int i = 0; i < 9; i++) {
                const int idx = atid + 96 * i;
                const int p = idx >> 5, ln = idx & 31, qd = ln & 3, l4 = ln >> 2;
                int kk, ecol;
                if (p < 22) {
                    kk = p < 3 ? 0 : p < 8 ? 1 : p < 14 ? 2 : p < 19 ? 3 : 4;
                    int nt = p < 3 ? p : p < 8 ? p - 3 : p < 14 ? p - 6 : p < 19 ? p - 9 : p - 12;
                    ecol = nt * 8 + l4;
                } else { kk = p - 22; ecol = -1; }
                float bv[4];
#pragma unroll
                for (int e = 0; e < 4; e++) {
                    int d = kk * 16 + 2 * qd + (e & 1) + (e >> 1) * 8, hd = d / 20;
                    if (ecol >= 0) bv[e] = (ecol / 20 == hd) ? kvf[d * 24 + ecol - hd * 20] : 0.f;
                    else bv[e] = (hd == l4) ? kvf[d * 24 + 20] : 0.f;
                }
                fr[i] = make_uint2(pack_bf16(bv[0], bv[1]), pack_bf16(bv[2], bv[3]));
            }
            named_bar(2, 96);
            uint2* kvf_s = (uint2*)(sgen + SM_KVF);
#pragma unroll
            for (int i = 0; i < 9; i++) kvf_s[atid + 96 * i] = fr[i];
            mbar_arrive(bar_kv);
            if (atid == 0) PROF(21);
            named_bar(6, 352);
            if (atid == 0) { red_release(&g_cnt.o[g1_m], 1); PROF(22); }
        } else if (c < 131) {
            G2Unit u1 = g2_unit(c, 1);
            g2_exchange(u1, sbase, bar_x, atid);
            named_bar(4, 352);
            if (atid == 0) red_release(&g_cnt.gflag[u1.tile], 1);
        }
      }
    } else {
        reg_alloc<200>();
        const int ctid = tid - 128, wg = ctid >> 7, wp = (ctid >> 5) & 3;
        if (ctid == 0) PROF(1);
        float acc[120], keep[32];
        int it = 0;
        g2_consume(u0, sbase, sgen, bar_full, bar_empty, it, acc, keep, wg, ctid);
        if (main_cta) {
            for (int k = 0; k < 10; k++, it++) {
                int s = it % NSTAGE;
                mbar_wait(bar_full + s * 8, (it / NSTAGE) & 1);
                uint32_t st = sbase + s * STAGE_BYTES;
                uint64_t da = desc_kmajor(st + wg * 8192), db = desc_mnmajor(st + B_OFF);
                wg_fence();
#pragma unroll
                for (int kk = 0; kk < 4; kk++) wgmma_n240<0, 1>(acc, da + kk * 2, db + kk * 128, (k | kk) != 0);
                wg_commit();
                if (k > 0) { wg_wait<1>(); if ((ctid & 127) == 0) mbar_arrive(bar_empty + ((it - 1) % NSTAGE) * 8); }
                if (k == K_FIN) g2_finalize(u0, P.b1, sgen, bar_x, 0, keep, wg, wp, lane, ctid);
            }
            wg_wait<0>();
            if ((ctid & 127) == 0) mbar_arrive(bar_empty + ((it - 1) % NSTAGE) * 8);
            if (ctid == 0) PROF(5);
            mbar_wait(bar_aux, 0);
            const int sslot = it % NSTAGE;
            mbar_wait(bar_full + sslot * 8, (it / NSTAGE) & 1);
            named_bar(1, 256);
            if (ctid == 0) PROF(6);
            __nv_bfloat16* pq_s = (__nv_bfloat16*)(sgen + SM_X);
            __nv_bfloat16* pk_s = (__nv_bfloat16*)(sgen + sslot * STAGE_BYTES);
            __nv_bfloat16* v_s = (__nv_bfloat16*)(sgen + sslot * STAGE_BYTES + TILE_BYTES);
            const float* cs_s = (const float*)(sgen + SM_CS);
            const float2* st_s = (const float2*)(sgen + SM_STATS);
            {
                const int r0 = wg * 64 + wp * 16 + (lane >> 2), cq = 2 * (lane & 3);
                const float2 s0 = st_s[r0], s1 = st_s[r0 + 8];
#pragma unroll
                for (int jj = 0; jj < 30; jj++) {
                    const int j = (jj + 10) % 30;
                    float2 cs = *(const float2*)(cs_s + 8 * j + cq);
                    float a0 = (acc[4 * j] - s0.x * cs.x) * s0.y, a1 = (acc[4 * j + 1] - s0.x * cs.y) * s0.y;
                    float a2 = (acc[4 * j + 2] - s1.x * cs.x) * s1.y, a3 = (acc[4 * j + 3] - s1.x * cs.y) * s1.y;
                    if (j < 20) {
                        a0 = fmaxf(a0, 0.f) + __expf(fminf(a0, 0.f)) + 1e-6f;
                        a1 = fmaxf(a1, 0.f) + __expf(fminf(a1, 0.f)) + 1e-6f;
                        a2 = fmaxf(a2, 0.f) + __expf(fminf(a2, 0.f)) + 1e-6f;
                        a3 = fmaxf(a3, 0.f) + __expf(fminf(a3, 0.f)) + 1e-6f;
                    }
                    __nv_bfloat16* dst = (j < 10) ? pq_s : (j < 20) ? pk_s : v_s;
                    int col = 8 * (j % 10) + cq;
                    *(uint32_t*)(dst + r0 * PQ_PITCH + col) = pack_bf16(a0, a1);
                    *(uint32_t*)(dst + (r0 + 8) * PQ_PITCH + col) = pack_bf16(a2, a3);
                }
            }
            named_bar(1, 256);
            if (ctid == 0) PROF(7);
            {
                const int w8 = ctid >> 5;
                const int mt = (w8 == 0) ? 0 : (w8 <= 2) ? 1 : (w8 <= 4) ? 2 : (w8 <= 6) ? 3 : 4;
                const int n0 = (w8 == 0) ? 0 : (w8 == 1) ? 0 : (w8 == 2) ? 3 : (w8 == 3) ? 2 : (w8 == 4) ? 6 : (w8 == 5) ? 5 : (w8 == 6) ? 8 : 7;
                const int nn = (w8 == 0 || w8 == 1 || w8 == 5 || w8 == 7) ? 3 : (w8 == 3) ? 4 : 2;
                const bool doz = (w8 == 0 || w8 == 2 || w8 == 4 || w8 == 6 || w8 == 7);
                float cacc[4][4], zacc[4];
#pragma unroll
                for (int i = 0; i < 4; i++) { cacc[i][0] = cacc[i][1] = cacc[i][2] = cacc[i][3] = 0.f; zacc[i] = 0.f; }
                const uint32_t pk_a = smem_u32(pk_s), v_a = smem_u32(v_s);
                const int lr = lane & 7, lm = lane >> 3;
#pragma unroll 2
                for (int ks = 0; ks < 8; ks++) {
                    uint32_t a[4];
                    ldsm_x4_t(a, pk_a + ((ks * 16 + (lm >> 1) * 8 + lr) * PQ_PITCH + mt * 16 + (lm & 1) * 8) * 2);
#pragma unroll
                    for (int i = 0; i < 4; i++) {
                        if (i < nn) {
                            uint32_t b[2];
                            ldsm_x2_t(b, v_a + ((ks * 16 + (lm & 1) * 8 + lr) * PQ_PITCH + (n0 + i) * 8) * 2);
                            mma16816(cacc[i], a, b[0], b[1]);
                        }
                    }
                    if (doz) mma16816(zacc, a, 0x3F803F80u, 0x3F803F80u);
                }
                float* kvp = &g_kvacc[g1_g][0];
                const int d0 = mt * 16 + (lane >> 2);
#pragma unroll
                for (int i = 0; i < 4; i++) {
                    if (i < nn) {
#pragma unroll
                        for (int e = 0; e < 4; e++) {
                            int d = d0 + (e >> 1) * 8, ec = (n0 + i) * 8 + 2 * (lane & 3) + (e & 1);
                            int hd = d / 20;
                            if (ec / 20 == hd) atomicAdd(kvp + d * 24 + ec - hd * 20, cacc[i][e]);
                        }
                    }
                }
                if (doz && (lane & 3) == 0) { atomicAdd(kvp + d0 * 24 + 20, zacc[0]); atomicAdd(kvp + (d0 + 8) * 24 + 20, zacc[2]); }
            }
            fence_proxy_async();
            named_arrive(5, 352);
            named_bar(1, 256);
            if ((ctid & 127) == 0) mbar_arrive(bar_empty + sslot * 8);
            if (ctid == 0) PROF(8);
            it++;
            for (int k = 0; k < f_nk; k++, it++) {
                int s = it % NSTAGE;
                mbar_wait(bar_full + s * 8, (it / NSTAGE) & 1);
                if (k == 0 && ctid == 0) PROF(9);
                uint32_t st = sbase + s * STAGE_BYTES;
                uint64_t db = desc_kmajor(st + B_OFF);
                wg_fence();
                if (k < f_nw2) {
                    uint64_t da = desc_mnmajor(st + wg * 8192);
#pragma unroll
                    for (int kk = 0; kk < 4; kk++) wgmma_n160<1, 0>(acc, da + kk * 128, db + kk * 2, (k | kk) != 0);
                } else {
                    uint64_t da = desc_kmajor(st + wg * 8192);
#pragma unroll
                    for (int kk = 0; kk < 4; kk++) wgmma_n160<0, 0>(acc, da + kk * 2, db + kk * 2, 1);
                }
                wg_commit();
                if (k > 0) { wg_wait<1>(); if ((ctid & 127) == 0) mbar_arrive(bar_empty + ((it - 1) % NSTAGE) * 8); }
                if (k == K_O) {
                    mbar_wait(bar_kv, 0);
                    if (ctid == 0) PROF(12);
                    const uint2* kvf_s = (const uint2*)(sgen + SM_KVF);
                    const int lr = lane & 7, lm = lane >> 3, qd = lane & 3, ln4 = lane >> 2;
                    const int m0 = (ctid >> 5) * 16;
                    uint32_t a[5][4];
#pragma unroll
                    for (int kk = 0; kk < 5; kk++) ldsm_x4(a[kk], sbase + SM_X + ((m0 + (lm & 1) * 8 + lr) * PQ_PITCH + kk * 16 + (lm >> 1) * 8) * 2);
                    float den[4] = {0.f, 0.f, 0.f, 0.f};
#pragma unroll
                    for (int kk = 0; kk < 5; kk++) { uint2 b = kvf_s[(22 + kk) * 32 + lane]; mma16816(den, a[kk], b.x, b.y); }
                    float dn[4][2];
#pragma unroll
                    for (int h = 0; h < 4; h++) {
                        int src = (lane & ~3) | (h >> 1);
                        float v0 = __shfl_sync(0xffffffffu, (h & 1) ? den[1] : den[0], src);
                        float v1 = __shfl_sync(0xffffffffu, (h & 1) ? den[3] : den[2], src);
                        dn[h][0] = __fdividef(1.0f, v0 + 1e-6f); dn[h][1] = __fdividef(1.0f, v1 + 1e-6f);
                    }
                    __nv_bfloat16* orow = g_o + (size_t)(g1_m * 128 + m0 + ln4) * D_ + g1_g * 80;
#pragma unroll
                    for (int nt = 0; nt < 10; nt++) {
                        float num[4] = {0.f, 0.f, 0.f, 0.f};
#pragma unroll
                        for (int kk = 0; kk < 5; kk++) {
                            const int first = kk == 0 ? 0 : kk == 1 ? 0 : kk == 2 ? 2 : kk == 3 ? 5 : 7;
                            const int cnt = kk == 0 ? 3 : kk == 1 ? 5 : kk == 2 ? 6 : kk == 3 ? 5 : 3;
                            const int off = kk == 0 ? 0 : kk == 1 ? 3 : kk == 2 ? 8 : kk == 3 ? 14 : 19;
                            if (nt >= first && nt < first + cnt) { uint2 b = kvf_s[(off + nt - first) * 32 + lane]; mma16816(num, a[kk], b.x, b.y); }
                        }
                        const int oc = nt * 8 + 2 * qd;
                        const int h0 = oc / 20;
                        float d00 = h0 == 0 ? dn[0][0] : h0 == 1 ? dn[1][0] : h0 == 2 ? dn[2][0] : dn[3][0];
                        float d01 = h0 == 0 ? dn[0][1] : h0 == 1 ? dn[1][1] : h0 == 2 ? dn[2][1] : dn[3][1];
                        *(uint32_t*)(orow + oc) = pack_bf16(num[0] * d00, num[1] * d00);
                        *(uint32_t*)(orow + 8 * D_ + oc) = pack_bf16(num[2] * d01, num[3] * d01);
                    }
                    fence_proxy_async();
                    named_arrive(6, 352);
                }
            }
            wg_wait<0>();
            if (ctid == 0) PROF(10);
            const int ftile = f_m * 4 + f_n;
            const int xs = it % NSTAGE;
            uint2* xb = (uint2*)(sgen + xs * STAGE_BYTES) + ctid;
            const int r0 = f_m * 128 + wg * 64 + wp * 16 + (lane >> 2), cb = f_n * 160 + 2 * (lane & 3);
            if (f_hh == 1) {
                const float bb0 = __bfloat162float(P.b2[r0]), bb1 = __bfloat162float(P.b2[r0 + 8]);
                uint32_t x0[20], x1[20];
#pragma unroll
                for (int q = 0; q < 20; q++) {
                    x0[q] = __ldg((const uint32_t*)(P.x + (size_t)r0 * D_ + cb + 8 * q));
                    x1[q] = __ldg((const uint32_t*)(P.x + (size_t)(r0 + 8) * D_ + cb + 8 * q));
                }
                named_bar(1, 256);
#pragma unroll
                for (int q = 0; q < 20; q++) {
                    xb[q * 256] = make_uint2(pack_bf16(acc[4 * q] + bf_lo(x0[q]) + bb0, acc[4 * q + 1] + bf_hi(x0[q]) + bb0),
                                             pack_bf16(acc[4 * q + 2] + bf_lo(x1[q]) + bb1, acc[4 * q + 3] + bf_hi(x1[q]) + bb1));
                }
                asm volatile("fence.proxy.async.shared::cta;" ::: "memory");
                named_bar(1, 256);
                if (ctid == 0) {
                    bulk_store(g_fpart + (size_t)ftile * (20 * 256), sbase + xs * STAGE_BYTES, 40960);
                    bulk_store_wait();
                    fence_proxy_async();
                    red_release(&g_cnt.fflag[ftile], 1);
                }
            } else {
                mbar_wait(bar_full + xs * 8, (it / NSTAGE) & 1);
#pragma unroll
                for (int q = 0; q < 20; q++) {
                    uint2 p = xb[q * 256];
                    *(uint32_t*)(P.out + (size_t)r0 * D_ + cb + 8 * q) = pack_bf16(acc[4 * q] + bf_lo(p.x), acc[4 * q + 1] + bf_hi(p.x));
                    *(uint32_t*)(P.out + (size_t)(r0 + 8) * D_ + cb + 8 * q) = pack_bf16(acc[4 * q + 2] + bf_lo(p.y), acc[4 * q + 3] + bf_hi(p.y));
                }
            }
            if (ctid == 0) PROF(11);
        } else {
            g2_finalize(u0, P.b1, sgen, bar_x, 0, keep, wg, wp, lane, ctid);
            if (c < 131) {
                named_bar(1, 256);
                G2Unit u1 = g2_unit(c, 1);
                g2_consume(u1, sbase, sgen, bar_full, bar_empty, it, acc, keep, wg, ctid);
                g2_finalize(u1, P.b1, sgen, bar_x, 1, keep, wg, wp, lane, ctid);
            }
        }
    }
    __syncthreads();
    unsigned* s_last = (unsigned*)(sgen + SM_BAR + 128);
    if (tid == 0) {
        __threadfence();
        *s_last = (atomicAdd(&g_cnt.done, 1) == 131);
    }
    __syncthreads();
    if (*s_last) {
        for (int i = tid; i < 8 * 1920; i += 384) (&g_kvacc[0][0])[i] = 0.f;
        for (int i = tid; i < (int)(sizeof(Counters) / 4); i += 384) ((unsigned*)&g_cnt)[i] = 0;
    }
}

typedef CUresult (*EncodeFn)(CUtensorMap*, CUtensorMapDataType, cuuint32_t, void*, const cuuint64_t*, const cuuint64_t*, const cuuint32_t*,
                             const cuuint32_t*, CUtensorMapInterleave, CUtensorMapSwizzle, CUtensorMapL2promotion, CUtensorMapFloatOOBfill);

bool make_map(EncodeFn enc, CUtensorMap* m, const void* ptr, int rank, const cuuint64_t* dims, const cuuint64_t* strides, const cuuint32_t* box) {
    cuuint32_t es[3] = {1, 1, 1};
    return enc(m, CU_TENSOR_MAP_DATA_TYPE_BFLOAT16, rank, (void*)ptr, dims, strides, box, es, CU_TENSOR_MAP_INTERLEAVE_NONE,
               CU_TENSOR_MAP_SWIZZLE_128B, CU_TENSOR_MAP_L2_PROMOTION_L2_128B, CU_TENSOR_MAP_FLOAT_OOB_FILL_NONE) == CUDA_SUCCESS;
}

struct HostState {
    bool ready;
    const void* key[4];
    CUtensorMap mX, mH, mW1, mW2, mO, mBF;
};
HostState g_hs;

}

extern "C" void kernel_launch(void* const* d_in, const int* in_sizes, int n_in, void* d_out, int out_size) {
    const __nv_bfloat16* x = (const __nv_bfloat16*)d_in[0];
    const __nv_bfloat16* wqkv = (const __nv_bfloat16*)d_in[1];
    const __nv_bfloat16* wo = (const __nv_bfloat16*)d_in[2];
    const __nv_bfloat16* w1 = (const __nv_bfloat16*)d_in[4];
    const __nv_bfloat16* b1 = (const __nv_bfloat16*)d_in[5];
    const __nv_bfloat16* w2 = (const __nv_bfloat16*)d_in[6];
    const __nv_bfloat16* b2 = (const __nv_bfloat16*)d_in[7];
    HostState& hs = g_hs;
    if (!hs.ready || hs.key[0] != x || hs.key[1] != w1 || hs.key[2] != w2) {
        void* fn = nullptr;
        cudaDriverEntryPointQueryResult qr;
        if (cudaGetDriverEntryPoint("cuTensorMapEncodeTiled", &fn, cudaEnableDefault, &qr) != cudaSuccess || !fn) return;
        EncodeFn enc = (EncodeFn)fn;
        void *ph, *pbf, *po;
        cudaGetSymbolAddress(&ph, g_h); cudaGetSymbolAddress(&pbf, g_BF); cudaGetSymbolAddress(&po, g_o);
        {
            cuuint64_t d[2] = {640, 2048}, s[1] = {1280}; cuuint32_t b[2] = {64, 128};
            make_map(enc, &hs.mX, x, 2, d, s, b);
            make_map(enc, &hs.mO, po, 2, d, s, b);
        }
        {
            cuuint64_t d[3] = {64, 2048, 10}, s[2] = {1280, 128}; cuuint32_t b[3] = {64, 64, 2};
            make_map(enc, &hs.mH, ph, 3, d, s, b);
        }
        {
            cuuint64_t d[3] = {64, 2048, 27}, s[2] = {3456, 128}; cuuint32_t b[3] = {64, 64, 3};
            make_map(enc, &hs.mW1, w1, 3, d, s, b);
        }
        {
            cuuint64_t d[3] = {64, 1728, 32}, s[2] = {4096, 128}; cuuint32_t b[3] = {64, 64, 2};
            make_map(enc, &hs.mW2, w2, 3, d, s, b);
        }
        {
            cuuint64_t d[2] = {2368, 640}, s[1] = {4736}; cuuint32_t b[2] = {64, 160};
            make_map(enc, &hs.mBF, pbf, 2, d, s, b);
        }
        cudaFuncSetAttribute(mega_kernel, cudaFuncAttributeMaxDynamicSharedMemorySize, SMEM_ALLOC);
        hs.key[0] = x; hs.key[1] = w1; hs.key[2] = w2;
        hs.ready = true;
    }
    Params P{x, wqkv, wo, b1, b2, (__nv_bfloat16*)d_out};
    mega_kernel<<<132, 384, SMEM_ALLOC>>>(hs.mX, hs.mH, hs.mW1, hs.mW2, hs.mO, hs.mBF, P);
}
```

```cpp
#include <cuda_runtime.h>
#include <cuda.h>
#include <cuda_bf16.h>
#include <stdint.h>

namespace {

constexpr int S_ = 2048, D_ = 640, F_ = 1728, KF_ = 2368;
constexpr int NSTAGE = 4;
constexpr int STAGE_BYTES = 47104;
constexpr int B_OFF = 16384;
constexpr int FSTAGE = 7, FSTAGE_BYTES = 26624;
constexpr int STG_OFF = 3 * STAGE_BYTES;
constexpr int PQ_PITCH = 88;
constexpr int TILE_BYTES = 128 * PQ_PITCH * 2;
constexpr int KVF_BYTES = 27 * 32 * 16;
constexpr int SM_X = NSTAGE * STAGE_BYTES;
constexpr int SM_KVF = SM_X + TILE_BYTES;
constexpr int SM_CS = SM_KVF + KVF_BYTES;
constexpr int SM_STATS = SM_CS + 960;
constexpr int SM_B1 = SM_STATS + 1024;
constexpr int SM_BAR = SM_B1 + 128;
constexpr int SMEM_ALLOC = SM_BAR + 256;

__device__ __align__(1024) __nv_bfloat16 g_h[S_ * D_];
__device__ __align__(1024) uint8_t g_BF[8 * 37 * 10240];
__device__ __align__(1024) __nv_bfloat16 g_o[S_ * D_];
__device__ __align__(1024) uint8_t g_wimg[8 * 10 * 30720];
__device__ __align__(128) float2 g_stats[S_];
__device__ __align__(128) float g_cs2[2][8][240];
__device__ __align__(1024) uint2 g_upart[45 * 3 * 2 * 2048];
__device__ __align__(128) float g_kvacc2[2][8][3456];

struct alignas(128) Ctr { unsigned v; unsigned pad[31]; };
struct Counters {
    Ctr hk[3];
    Ctr cs[8];
    Ctr prep;
    Ctr uflag[45];
    Ctr gd[5];
    Ctr gdl[5];
    Ctr kv[8];
    Ctr o[16];
};
__device__ Counters g_cnt2[2];
__device__ unsigned g_done;
#define FAIL(code) __trap()
#define MBAR_LIMIT (1u << 24)
#define SPIN_LIMIT (1u << 22)
#define PROF(i)
#define PROFD(i, v)

__device__ __forceinline__ uint32_t smem_u32(const void* p) { return (uint32_t)__cvta_generic_to_shared(p); }
__device__ __forceinline__ void mbar_init(uint32_t bar, uint32_t cnt) { asm volatile("mbarrier.init.shared::cta.b64 [%0], %1;" ::"r"(bar), "r"(cnt)); }
__device__ __forceinline__ void mbar_expect_tx(uint32_t bar, uint32_t bytes) { asm volatile("mbarrier.arrive.expect_tx.shared::cta.b64 _, [%0], %1;" ::"r"(bar), "r"(bytes) : "memory"); }
__device__ __forceinline__ void mbar_arrive(uint32_t bar) { asm volatile("mbarrier.arrive.shared::cta.b64 _, [%0];" ::"r"(bar) : "memory"); }
__device__ __forceinline__ void mbar_wait(uint32_t bar, uint32_t parity) {
    uint32_t done = 0;
#pragma unroll 1
    for (uint32_t i = 0; i < MBAR_LIMIT; i++) {
        asm volatile("{\n.reg .pred p;\nmbarrier.try_wait.parity.shared::cta.b64 p, [%1], %2;\nselp.u32 %0, 1, 0, p;\n}" : "=r"(done) : "r"(bar), "r"(parity) : "memory");
        if (done) return;
    }
    FAIL(100 + ((bar >> 3) & 15));
}
__device__ __forceinline__ void tma2d(uint32_t dst, const CUtensorMap* m, uint32_t bar, int c0, int c1) {
    asm volatile("cp.async.bulk.tensor.2d.shared::cluster.global.mbarrier::complete_tx::bytes [%0], [%1, {%3, %4}], [%2];"
                 ::"r"(dst), "l"((uint64_t)m), "r"(bar), "r"(c0), "r"(c1) : "memory");
}
__device__ __forceinline__ void tma3d(uint32_t dst, const CUtensorMap* m, uint32_t bar, int c0, int c1, int c2) {
    asm volatile("cp.async.bulk.tensor.3d.shared::cluster.global.mbarrier::complete_tx::bytes [%0], [%1, {%3, %4, %5}], [%2];"
                 ::"r"(dst), "l"((uint64_t)m), "r"(bar), "r"(c0), "r"(c1), "r"(c2) : "memory");
}
__device__ __forceinline__ void bulk_store(void* gdst, uint32_t ssrc, uint32_t bytes) {
    asm volatile("cp.async.bulk.global.shared::cta.bulk_group [%0], [%1], %2;" ::"l"(gdst), "r"(ssrc), "r"(bytes) : "memory");
}
__device__ __forceinline__ void bulk_reduce_add_f32(void* gdst, uint32_t ssrc, uint32_t bytes) {
    asm volatile("cp.reduce.async.bulk.global.shared::cta.bulk_group.add.f32 [%0], [%1], %2;" ::"l"(gdst), "r"(ssrc), "r"(bytes) : "memory");
}
__device__ __forceinline__ void sts128(uint32_t addr, float a, float b, float c, float d) {
    asm volatile("st.shared.v4.f32 [%0], {%1, %2, %3, %4};" ::"r"(addr), "f"(a), "f"(b), "f"(c), "f"(d) : "memory");
}
__device__ __forceinline__ float4 lds128(uint32_t addr) {
    float4 v;
    asm volatile("ld.shared.v4.f32 {%0, %1, %2, %3}, [%4];" : "=f"(v.x), "=f"(v.y), "=f"(v.z), "=f"(v.w) : "r"(addr) : "memory");
    return v;
}
__device__ __forceinline__ float2 lds64_c(uint32_t addr) {
    float2 v;
    asm("ld.shared.v2.f32 {%0, %1}, [%2];" : "=f"(v.x), "=f"(v.y) : "r"(addr));
    return v;
}
__device__ __forceinline__ float4 lds128_c(uint32_t addr) {
    float4 v;
    asm("ld.shared.v4.f32 {%0, %1, %2, %3}, [%4];" : "=f"(v.x), "=f"(v.y), "=f"(v.z), "=f"(v.w) : "r"(addr));
    return v;
}
__device__ __forceinline__ uint32_t launder(uint32_t v) {
    uint32_t r;
    asm volatile("mov.u32 %0, %1;" : "=r"(r) : "r"(v) : "memory");
    return r;
}
__device__ __forceinline__ void sts32(uint32_t addr, uint32_t v) { asm volatile("st.shared.b32 [%0], %1;" ::"r"(addr), "r"(v)); }
__device__ __forceinline__ void bulk_store_wait() {
    asm volatile("cp.async.bulk.commit_group;" ::: "memory");
    asm volatile("cp.async.bulk.wait_group 0;" ::: "memory");
}
__device__ __forceinline__ void bulk_load(uint32_t sdst, const void* gsrc, uint32_t bytes, uint32_t bar) {
    asm volatile("cp.async.bulk.shared::cluster.global.mbarrier::complete_tx::bytes [%0], [%1], %2, [%3];" ::"r"(sdst), "l"(gsrc), "r"(bytes), "r"(bar) : "memory");
}
__device__ __forceinline__ void l2_prefetch(const void* g, uint32_t bytes) {
    asm volatile("cp.async.bulk.prefetch.L2.global [%0], %1;" ::"l"(g), "r"(bytes) : "memory");
}
__device__ __forceinline__ bool elect_one() {
    uint32_t pred;
    asm volatile("{\n.reg .pred p;\nelect.sync _|p, 0xffffffff;\nselp.u32 %0, 1, 0, p;\n}" : "=r"(pred));
    return pred != 0;
}
__device__ __forceinline__ void named_arrive(int id, int n) { asm volatile("bar.arrive %0, %1;" ::"r"(id), "r"(n) : "memory"); }
__device__ __forceinline__ unsigned ld_acquire(const unsigned* p) {
    unsigned v;
    asm volatile("ld.acquire.gpu.global.u32 %0, [%1];" : "=r"(v) : "l"(p) : "memory");
    return v;
}
__device__ __forceinline__ void red_release(Ctr* p, unsigned v) {
    asm volatile("red.release.gpu.global.add.u32 [%0], %1;" ::"l"(&p->v), "r"(v) : "memory");
}
__device__ __forceinline__ void red_relaxed(Ctr* p, unsigned v) {
    asm volatile("red.release.gpu.global.add.u32 [%0], %1;" ::"l"(&p->v), "r"(v) : "memory");
}
__device__ __forceinline__ void tma_store2d(const CUtensorMap* m, uint32_t ssrc, int c0, int c1) {
    asm volatile("cp.async.bulk.tensor.2d.global.shared::cta.bulk_group [%0, {%2, %3}], [%1];" ::"l"((uint64_t)m), "r"(ssrc), "r"(c0), "r"(c1) : "memory");
}
__device__ __forceinline__ void spin_ge(const Ctr* cp, unsigned target) {
    const unsigned* p = &cp->v;
#pragma unroll 1
    for (uint32_t i = 0; i < SPIN_LIMIT; i++) {
        if (ld_acquire(p) >= target) return;
        __nanosleep(40);
    }
    FAIL(1000 + (int)((p - (const unsigned*)&g_cnt2[0]) >> 5));
}
__device__ __forceinline__ void fence_proxy_async() { asm volatile("fence.proxy.async;" ::: "memory"); }
__device__ __forceinline__ void reader_fence() {
}
__device__ __forceinline__ void named_bar(int id, int n) { asm volatile("bar.sync %0, %1;" ::"r"(id), "r"(n) : "memory"); }
__device__ __forceinline__ void wg_fence() { asm volatile("wgmma.fence.sync.aligned;" ::: "memory"); }
__device__ __forceinline__ void wg_commit() { asm volatile("wgmma.commit_group.sync.aligned;" ::: "memory"); }
template <int N> __device__ __forceinline__ void wg_wait() { asm volatile("wgmma.wait_group.sync.aligned %0;" ::"n"(N) : "memory"); }
template <int R> __device__ __forceinline__ void reg_alloc() { asm volatile("setmaxnreg.inc.sync.aligned.u32 %0;" ::"n"(R)); }
template <int R> __device__ __forceinline__ void reg_dealloc() { asm volatile("setmaxnreg.dec.sync.aligned.u32 %0;" ::"n"(R)); }

__device__ __forceinline__ uint64_t desc_kmajor(uint32_t addr) {
    return (uint64_t)((addr & 0x3FFFF) >> 4) | ((uint64_t)1 << 16) | ((uint64_t)64 << 32) | ((uint64_t)1 << 62);
}
__device__ __forceinline__ uint64_t desc_mnmajor(uint32_t addr) {
    return (uint64_t)((addr & 0x3FFFF) >> 4) | ((uint64_t)512 << 16) | ((uint64_t)64 << 32) | ((uint64_t)1 << 62);
}
__device__ __forceinline__ uint64_t desc_mnmajor32(uint32_t addr) {
    return (uint64_t)((addr & 0x3FFFF) >> 4) | ((uint64_t)128 << 16) | ((uint64_t)16 << 32) | ((uint64_t)3 << 62);
}
__device__ __forceinline__ uint32_t pack_bf16(float a, float b) {
    uint32_t r;
    asm("cvt.rn.bf16x2.f32 %0, %1, %2;" : "=r"(r) : "f"(b), "f"(a));
    return r;
}
__device__ __forceinline__ float bf_lo(uint32_t v) { return __uint_as_float(v << 16); }
__device__ __forceinline__ float bf_hi(uint32_t v) { return __uint_as_float(v & 0xFFFF0000u); }
__device__ __forceinline__ void ldsm_x4(uint32_t (&r)[4], uint32_t addr) {
    asm volatile("ldmatrix.sync.aligned.m8n8.x4.shared.b16 {%0,%1,%2,%3}, [%4];" : "=r"(r[0]), "=r"(r[1]), "=r"(r[2]), "=r"(r[3]) : "r"(addr) : "memory");
}
__device__ __forceinline__ void ldsm_x4_t(uint32_t (&r)[4], uint32_t addr) {
    asm volatile("ldmatrix.sync.aligned.m8n8.x4.trans.shared.b16 {%0,%1,%2,%3}, [%4];" : "=r"(r[0]), "=r"(r[1]), "=r"(r[2]), "=r"(r[3]) : "r"(addr) : "memory");
}
__device__ __forceinline__ void ldsm_x2_t(uint32_t (&r)[2], uint32_t addr) {
    asm volatile("ldmatrix.sync.aligned.m8n8.x2.trans.shared.b16 {%0,%1}, [%2];" : "=r"(r[0]), "=r"(r[1]) : "r"(addr) : "memory");
}
__device__ __forceinline__ void mma16816(float (&c)[4], const uint32_t (&a)[4], uint32_t b0, uint32_t b1) {
    asm volatile("mma.sync.aligned.m16n8k16.row.col.f32.bf16.bf16.f32 {%0,%1,%2,%3}, {%4,%5,%6,%7}, {%8,%9}, {%0,%1,%2,%3};"
                 : "+f"(c[0]), "+f"(c[1]), "+f"(c[2]), "+f"(c[3]) : "r"(a[0]), "r"(a[1]), "r"(a[2]), "r"(a[3]), "r"(b0), "r"(b1));
}
__device__ __forceinline__ void sts32_p(uint32_t addr, uint32_t v, uint32_t live) {
    asm volatile("{\n.reg .pred p;\nsetp.ne.u32 p, %2, 0;\n@p st.shared.b32 [%0], %1;\n}" ::"r"(addr), "r"(v), "r"(live) : "memory");
}
__device__ __forceinline__ void sts64_p(uint32_t addr, uint32_t v0, uint32_t v1, uint32_t live) {
    asm volatile("{\n.reg .pred p;\nsetp.ne.u32 p, %3, 0;\n@p st.shared.v2.b32 [%0], {%1, %2};\n}" ::"r"(addr), "r"(v0), "r"(v1), "r"(live) : "memory");
}
__device__ __forceinline__ void stg32_p(void* ptr, uint32_t v, uint32_t live) {
    asm volatile("{\n.reg .pred p;\nsetp.ne.u32 p, %2, 0;\n@p st.global.b32 [%0], %1;\n}" ::"l"(ptr), "r"(v), "r"(live) : "memory");
}
__device__ __forceinline__ void redf_p(float* ptr, float v, uint32_t live) {
    asm volatile("{\n.reg .pred p;\nsetp.ne.u32 p, %2, 0;\n@p red.global.add.f32 [%0], %1;\n}" ::"l"(ptr), "f"(v), "r"(live) : "memory");
}
__device__ __forceinline__ float gelu_tanh(float u) {
    float z = u * fmaf(0.044715f * 0.7978845608028654f * u, u, 0.7978845608028654f), t;
    asm("tanh.approx.f32 %0, %1;" : "=f"(t) : "f"(z));
    float hu = 0.5f * u;
    return fmaf(hu, t, hu);
}

template<int TA, int TB>
__device__ __forceinline__ void wgmma_n80(float (&d)[40], uint64_t da, uint64_t db, int scale_d) {
    asm volatile("{\n.reg .pred p;\nsetp.ne.b32 p, %42, 0;\n"
        "wgmma.mma_async.sync.aligned.m64n80k16.f32.bf16.bf16 "
        "{%0, %1, %2, %3, %4, %5, %6, %7, %8, %9, %10, %11, %12, %13, %14, %15, "
        "%16, %17, %18, %19, %20, %21, %22, %23, %24, %25, %26, %27, %28, %29, %30, %31, "
        "%32, %33, %34, %35, %36, %37, %38, %39}, "
        "%40, %41, p, 1, 1, %43, %44;\n}\n"
        : "+f"(d[0]), "+f"(d[1]), "+f"(d[2]), "+f"(d[3]), "+f"(d[4]), "+f"(d[5]), "+f"(d[6]), "+f"(d[7]),
          "+f"(d[8]), "+f"(d[9]), "+f"(d[10]), "+f"(d[11]), "+f"(d[12]), "+f"(d[13]), "+f"(d[14]), "+f"(d[15]),
          "+f"(d[16]), "+f"(d[17]), "+f"(d[18]), "+f"(d[19]), "+f"(d[20]), "+f"(d[21]), "+f"(d[22]), "+f"(d[23]),
          "+f"(d[24]), "+f"(d[25]), "+f"(d[26]), "+f"(d[27]), "+f"(d[28]), "+f"(d[29]), "+f"(d[30]), "+f"(d[31]),
          "+f"(d[32]), "+f"(d[33]), "+f"(d[34]), "+f"(d[35]), "+f"(d[36]), "+f"(d[37]), "+f"(d[38]), "+f"(d[39])
        : "l"(da), "l"(db), "r"(scale_d), "n"(TA), "n"(TB));
}

template<int TA, int TB>
__device__ __forceinline__ void wgmma_n192(float (&d)[120], uint64_t da, uint64_t db, int scale_d) {
    asm volatile("{\n.reg .pred p;\nsetp.ne.b32 p, %98, 0;\n"
        "wgmma.mma_async.sync.aligned.m64n192k16.f32.bf16.bf16 "
        "{%0, %1, %2, %3, %4, %5, %6, %7, %8, %9, %10, %11, %12, %13, %14, %15, "
        "%16, %17, %18, %19, %20, %21, %22, %23, %24, %25, %26, %27, %28, %29, %30, %31, "
        "%32, %33, %34, %35, %36, %37, %38, %39, %40, %41, %42, %43, %44, %45, %46, %47, "
        "%48, %49, %50, %51, %52, %53, %54, %55, %56, %57, %58, %59, %60, %61, %62, %63, "
        "%64, %65, %66, %67, %68, %69, %70, %71, %72, %73, %74, %75, %76, %77, %78, %79, "
        "%80, %81, %82, %83, %84, %85, %86, %87, %88, %89, %90, %91, %92, %93, %94, %95}, "
        "%96, %97, p, 1, 1, %99, %100;\n}\n"
        : "+f"(d[0]), "+f"(d[1]), "+f"(d[2]), "+f"(d[3]), "+f"(d[4]), "+f"(d[5]), "+f"(d[6]), "+f"(d[7]),
          "+f"(d[8]), "+f"(d[9]), "+f"(d[10]), "+f"(d[11]), "+f"(d[12]), "+f"(d[13]), "+f"(d[14]), "+f"(d[15]),
          "+f"(d[16]), "+f"(d[17]), "+f"(d[18]), "+f"(d[19]), "+f"(d[20]), "+f"(d[21]), "+f"(d[22]), "+f"(d[23]),
          "+f"(d[24]), "+f"(d[25]), "+f"(d[26]), "+f"(d[27]), "+f"(d[28]), "+f"(d[29]), "+f"(d[30]), "+f"(d[31]),
          "+f"(d[32]), "+f"(d[33]), "+f"(d[34]), "+f"(d[35]), "+f"(d[36]), "+f"(d[37]), "+f"(d[38]), "+f"(d[39]),
          "+f"(d[40]), "+f"(d[41]), "+f"(d[42]), "+f"(d[43]), "+f"(d[44]), "+f"(d[45]), "+f"(d[46]), "+f"(d[47]),
          "+f"(d[48]), "+f"(d[49]), "+f"(d[50]), "+f"(d[51]), "+f"(d[52]), "+f"(d[53]), "+f"(d[54]), "+f"(d[55]),
          "+f"(d[56]), "+f"(d[57]), "+f"(d[58]), "+f"(d[59]), "+f"(d[60]), "+f"(d[61]), "+f"(d[62]), "+f"(d[63]),
          "+f"(d[64]), "+f"(d[65]), "+f"(d[66]), "+f"(d[67]), "+f"(d[68]), "+f"(d[69]), "+f"(d[70]), "+f"(d[71]),
          "+f"(d[72]), "+f"(d[73]), "+f"(d[74]), "+f"(d[75]), "+f"(d[76]), "+f"(d[77]), "+f"(d[78]), "+f"(d[79]),
          "+f"(d[80]), "+f"(d[81]), "+f"(d[82]), "+f"(d[83]), "+f"(d[84]), "+f"(d[85]), "+f"(d[86]), "+f"(d[87]),
          "+f"(d[88]), "+f"(d[89]), "+f"(d[90]), "+f"(d[91]), "+f"(d[92]), "+f"(d[93]), "+f"(d[94]), "+f"(d[95])
        : "l"(da), "l"(db), "r"(scale_d), "n"(TA), "n"(TB));
}

template<int TA, int TB>
__device__ __forceinline__ void wgmma_n240(float (&d)[120], uint64_t da, uint64_t db, int scale_d) {
    asm volatile("{\n.reg .pred p;\nsetp.ne.b32 p, %122, 0;\n"
        "wgmma.mma_async.sync.aligned.m64n240k16.f32.bf16.bf16 "
        "{%0, %1, %2, %3, %4, %5, %6, %7, %8, %9, %10, %11, %12, %13, %14, %15, "
        "%16, %17, %18, %19, %20, %21, %22, %23, %24, %25, %26, %27, %28, %29, %30, %31, "
        "%32, %33, %34, %35, %36, %37, %38, %39, %40, %41, %42, %43, %44, %45, %46, %47, "
        "%48, %49, %50, %51, %52, %53, %54, %55, %56, %57, %58, %59, %60, %61, %62, %63, "
        "%64, %65, %66, %67, %68, %69, %70, %71, %72, %73, %74, %75, %76, %77, %78, %79, "
        "%80, %81, %82, %83, %84, %85, %86, %87, %88, %89, %90, %91, %92, %93, %94, %95, "
        "%96, %97, %98, %99, %100, %101, %102, %103, %104, %105, %106, %107, %108, %109, %110, %111, "
        "%112, %113, %114, %115, %116, %117, %118, %119}, "
        "%120, %121, p, 1, 1, %123, %124;\n}\n"
        : "+f"(d[0]), "+f"(d[1]), "+f"(d[2]), "+f"(d[3]), "+f"(d[4]), "+f"(d[5]), "+f"(d[6]), "+f"(d[7]),
          "+f"(d[8]), "+f"(d[9]), "+f"(d[10]), "+f"(d[11]), "+f"(d[12]), "+f"(d[13]), "+f"(d[14]), "+f"(d[15]),
          "+f"(d[16]), "+f"(d[17]), "+f"(d[18]), "+f"(d[19]), "+f"(d[20]), "+f"(d[21]), "+f"(d[22]), "+f"(d[23]),
          "+f"(d[24]), "+f"(d[25]), "+f"(d[26]), "+f"(d[27]), "+f"(d[28]), "+f"(d[29]), "+f"(d[30]), "+f"(d[31]),
          "+f"(d[32]), "+f"(d[33]), "+f"(d[34]), "+f"(d[35]), "+f"(d[36]), "+f"(d[37]), "+f"(d[38]), "+f"(d[39]),
          "+f"(d[40]), "+f"(d[41]), "+f"(d[42]), "+f"(d[43]), "+f"(d[44]), "+f"(d[45]), "+f"(d[46]), "+f"(d[47]),
          "+f"(d[48]), "+f"(d[49]), "+f"(d[50]), "+f"(d[51]), "+f"(d[52]), "+f"(d[53]), "+f"(d[54]), "+f"(d[55]),
          "+f"(d[56]), "+f"(d[57]), "+f"(d[58]), "+f"(d[59]), "+f"(d[60]), "+f"(d[61]), "+f"(d[62]), "+f"(d[63]),
          "+f"(d[64]), "+f"(d[65]), "+f"(d[66]), "+f"(d[67]), "+f"(d[68]), "+f"(d[69]), "+f"(d[70]), "+f"(d[71]),
          "+f"(d[72]), "+f"(d[73]), "+f"(d[74]), "+f"(d[75]), "+f"(d[76]), "+f"(d[77]), "+f"(d[78]), "+f"(d[79]),
          "+f"(d[80]), "+f"(d[81]), "+f"(d[82]), "+f"(d[83]), "+f"(d[84]), "+f"(d[85]), "+f"(d[86]), "+f"(d[87]),
          "+f"(d[88]), "+f"(d[89]), "+f"(d[90]), "+f"(d[91]), "+f"(d[92]), "+f"(d[93]), "+f"(d[94]), "+f"(d[95]),
          "+f"(d[96]), "+f"(d[97]), "+f"(d[98]), "+f"(d[99]), "+f"(d[100]), "+f"(d[101]), "+f"(d[102]), "+f"(d[103]),
          "+f"(d[104]), "+f"(d[105]), "+f"(d[106]), "+f"(d[107]), "+f"(d[108]), "+f"(d[109]), "+f"(d[110]), "+f"(d[111]),
          "+f"(d[112]), "+f"(d[113]), "+f"(d[114]), "+f"(d[115]), "+f"(d[116]), "+f"(d[117]), "+f"(d[118]), "+f"(d[119])
        : "l"(da), "l"(db), "r"(scale_d), "n"(TA), "n"(TB));
}

struct Params {
    const __nv_bfloat16* x;
    const __nv_bfloat16* wqkv;
    const __nv_bfloat16* wo;
    const __nv_bfloat16* b1;
    const __nv_bfloat16* b2;
    const __nv_bfloat16* w2;
    __nv_bfloat16* out;
};

struct G2Unit { int dt, ft, ks, kb0, nk, tile; };
__device__ __forceinline__ G2Unit g2_unit(int c, int round) {
    G2Unit u;
    if (round == 0) {
        const int p = c >> 1, r = c & 1;
        const int i = p < 64 ? (p & 7) * 8 + (p >> 3) : p;
        u.ks = i / 22;
        const int j = i % 22;
        if (j < 18) { u.ft = j >> 1; u.dt = 2 * (j & 1) + r; }
        else { u.dt = 4; u.ft = 2 * (j - 18) + r; }
    } else { u.dt = 4; u.ft = 8; u.ks = (c - 128) % 3; }
    u.kb0 = u.ks * 11; u.nk = (u.ks == 2) ? 10 : 11; u.tile = u.dt * 9 + u.ft;
    return u;
}

constexpr int F_NK = 37;
#define K_FIN_V 8
constexpr int K_FIN = K_FIN_V;
#define K_O_V 16
constexpr int K_O = K_O_V;
#define F_EARLY 5

__device__ __forceinline__ void g2_run(const G2Unit& u, bool prof, uint32_t sbase, uint8_t* sgen, int ctid, int& cs_, int& cph, float (&acc)[120], float (&keep)[32]) {
    const uint32_t bar_full = sbase + SM_BAR, bar_empty = bar_full + 32, bar_x = bar_full + 72;
    const int wg = ctid >> 7, wp = (ctid >> 5) & 3, lane = ctid & 31;
    const bool wl = (ctid & 127) == 0;
    (void)bar_full; (void)bar_empty; (void)bar_x; (void)wg; (void)wp; (void)lane; (void)wl;

#pragma unroll 1
            for (int k = 0; k < u.nk; k++) {
                mbar_wait(bar_full + cs_ * 8, cph);
                if (prof && k == 0 && ctid == 0) PROF(2);
                uint32_t st = sbase + cs_ * STAGE_BYTES;
                uint64_t da = desc_mnmajor(st + wg * 8192), db = desc_mnmajor(st + B_OFF);
                wg_fence();
#pragma unroll
                for (int kk = 0; kk < 4; kk++) wgmma_n192<1, 1>(acc, da + kk * 128, db + kk * 128, (k | kk) != 0);
                wg_commit();
                wg_wait<1>();
                if (k > 0 && wl) mbar_arrive(bar_empty + ((cs_ + NSTAGE - 1) % NSTAGE) * 8);
                if (++cs_ == NSTAGE) { cs_ = 0; cph ^= 1; }
            }
            wg_wait<0>();
            if (wl) mbar_arrive(bar_empty + ((cs_ + NSTAGE - 1) % NSTAGE) * 8);
            if (prof && ctid == 0) PROF(3);
            uint2* rem = (uint2*)(sgen + SM_X) + ctid;
#pragma unroll
            for (int t3 = 0; t3 < 3; t3++) {
                if (t3 == u.ks) {
#pragma unroll
                    for (int j = 0; j < 32; j++) keep[j] = acc[32 * t3 + j];
                } else {
                    uint2* r = rem + ((t3 > u.ks) ? t3 - 1 : t3) * 2048;
#pragma unroll
                    for (int q = 0; q < 8; q++) { const int j = 4 * (8 * t3 + q); r[q * 256] = make_uint2(pack_bf16(acc[j], acc[j + 1]), pack_bf16(acc[j + 2], acc[j + 3])); }
                }
            }
            asm volatile("fence.proxy.async.shared::cta;" ::: "memory");
            named_arrive(3, 352);
            if (prof && ctid == 0) PROF(4);
        }

__device__ __forceinline__ void g2_fin(const G2Unit& u, int xpar, uint32_t sbase, uint8_t* sgen, int ctid, const float (&keep)[32]) {
    const uint32_t bar_full = sbase + SM_BAR, bar_empty = bar_full + 32, bar_x = bar_full + 72;
    const int wg = ctid >> 7, wp = (ctid >> 5) & 3, lane = ctid & 31;
    const bool wl = (ctid & 127) == 0;
    (void)bar_full; (void)bar_empty; (void)bar_x; (void)wg; (void)wp; (void)lane; (void)wl;

            if (ctid == 0) PROF(58);
            mbar_wait(bar_x, xpar);
            if (ctid == 0) PROF(59);
            const int r0 = wg * 64 + wp * 16 + (lane >> 2);
            const uint2* rem = (const uint2*)(sgen + SM_X) + ctid;
            const uint32_t* b1s = (const uint32_t*)(sgen + SM_B1) + (lane & 3);
            uint32_t gv[16];
#pragma unroll
            for (int q = 0; q < 8; q++) {
                const uint2 b = rem[q * 256], cc = rem[2048 + q * 256];
                const uint32_t bb = b1s[4 * q];
                const float bl = bf_lo(bb), bh = bf_hi(bb);
                float u0 = gelu_tanh(keep[4 * q] + bf_lo(b.x) + bf_lo(cc.x) + bl), u1 = gelu_tanh(keep[4 * q + 1] + bf_hi(b.x) + bf_hi(cc.x) + bh);
                float u2 = gelu_tanh(keep[4 * q + 2] + bf_lo(b.y) + bf_lo(cc.y) + bl), u3 = gelu_tanh(keep[4 * q + 3] + bf_hi(b.y) + bf_hi(cc.y) + bh);
                gv[2 * q] = pack_bf16(u0, u1); gv[2 * q + 1] = pack_bf16(u2, u3);
            }
            if (ctid == 0) PROF(60);
            named_bar(1, 256);
            const uint32_t gs = sbase + SM_X + r0 * 128 + (lane & 3) * 4;
#pragma unroll
            for (int q = 0; q < 8; q++) {
                asm volatile("st.shared.b32 [%0], %1;" ::"r"(gs + ((q ^ (r0 & 7)) << 4)), "r"(gv[2 * q]) : "memory");
                asm volatile("st.shared.b32 [%0], %1;" ::"r"(gs + 1024 + ((q ^ (r0 & 7)) << 4)), "r"(gv[2 * q + 1]) : "memory");
            }
            asm volatile("fence.proxy.async.shared::cta;" ::: "memory");
            named_arrive(4, 352);
            if (ctid == 0) PROF(61);
        }

__device__ __forceinline__ void leftover_consumer(int c, int nrounds, uint32_t sbase, uint8_t* sgen, int ctid) {
    float acc[120], keep[32];
    int cs_ = 0, cph = 0;
#pragma unroll 1
    for (int round = 0; round < nrounds; round++) {
        const G2Unit u = g2_unit(c, round);
        g2_run(u, round == 0, sbase, sgen, ctid, cs_, cph, acc, keep);
        g2_fin(u, round & 1, sbase, sgen, ctid, keep);
        mbar_wait(sbase + SM_BAR + 96, round & 1);
    }
}

__global__ void __cluster_dims__(2, 1, 1) __launch_bounds__(384, 1)
mega_kernel(const __grid_constant__ CUtensorMap mX, const __grid_constant__ CUtensorMap mH, const __grid_constant__ CUtensorMap mW1,
            const __grid_constant__ CUtensorMap mW2, const __grid_constant__ CUtensorMap mO, const __grid_constant__ CUtensorMap mXr, const __grid_constant__ CUtensorMap mOut, const Params P) {
    extern __shared__ __align__(1024) uint8_t smem_raw[];
    uint32_t sbase;
    asm volatile("mov.u32 %0, %1;" : "=r"(sbase) : "r"(smem_u32(smem_raw)));
    uint8_t* sgen = smem_raw;
    const uint32_t bar_full = sbase + SM_BAR, bar_empty = bar_full + 32, bar_aux = bar_full + 64, bar_x = bar_full + 72, bar_kv = bar_full + 80, bar_prep = bar_full + 88, bar_gs = bar_full + 96, bar_stg = bar_full + 104, bar_xr = bar_full + 120, bar_ff = bar_full + 128, bar_fe = bar_full + 192;
    const int tid = threadIdx.x, warp = tid >> 5, lane = tid & 31;
    const int c = blockIdx.x;
    const bool main_cta = c < 128;
    const int nrounds = (c >= 128 && c < 131) ? 2 : 1;
    if (tid == 0) PROF(0);
    unsigned done0;
    asm volatile("ld.relaxed.gpu.global.u32 %0, [%1];" : "=r"(done0) : "l"(&g_done) : "memory");
    const int par = done0 >= 132;
    Counters& g_cnt = g_cnt2[par];
    float (*g_cs)[240] = g_cs2[par];
    float (*g_kvacc)[3456] = g_kvacc2[par];
    const long long prof0_dummy = 0;

    const int hl = lane & 15;
    const int ln_row = c * 16 + (warp - 4) * 2 + (lane >> 4);
    uint4 xv[5];
    if (main_cta && warp >= 4) {
        const uint4* xr = (const uint4*)(P.x + (size_t)ln_row * D_);
#pragma unroll
        for (int i = 0; i < 5; i++) xv[i] = __ldg(xr + hl + 16 * i);
    }
    const int g1_g = (c >> 1) & 7, g1_m = 2 * ((c >> 4) & 7) + (c & 1);
    if (tid == 0) {
        if (sbase & 1023) __trap();
        for (int i = 0; i < NSTAGE; i++) { mbar_init(bar_full + i * 8, 1); mbar_init(bar_empty + i * 8, 2); }
        mbar_init(bar_aux, 1);
        mbar_init(bar_x, 1);
        mbar_init(bar_kv, 1);
        mbar_init(bar_prep, 1);
        mbar_init(bar_gs, 1);
        mbar_init(bar_stg, 2);
        mbar_init(bar_xr, 1);
        for (int i = 0; i < FSTAGE; i++) { mbar_init(bar_ff + i * 8, 1); mbar_init(bar_fe + i * 8, 2); }
        asm volatile("fence.mbarrier_init.release.cluster;" ::: "memory");
        const G2Unit u0 = g2_unit(c, 0);
#pragma unroll 1
        for (int k = 0; k < 2; k++) {
            uint32_t fb = bar_full + k * 8;
            mbar_expect_tx(fb, 16384 + 24576);
            tma3d(sbase + k * STAGE_BYTES + B_OFF, &mW1, fb, 0, (u0.kb0 + k) * 64, u0.ft * 3);
        }
    }
    __syncthreads();
    if (tid == 128) PROF(15);

    const int pr = c >> 1, rk = c & 1;
    const int f_m = 2 * (pr & 7) + ((pr >> 3) & 1), f_n = ((pr >> 4) & 3) * 2 + rk;

    if (warp >= 4 && !main_cta) {
        reg_alloc<200>();
        leftover_consumer(c, nrounds, sbase, sgen, tid - 128);
    } else if (warp < 4) {
      reg_dealloc<96>();
      if (warp == 0) {
        if (elect_one()) {
            int s = 0, ph = 1, cnt = 0;
            auto next = [&]() { cnt++; if (++s == NSTAGE) { s = 0; ph ^= 1; } };
#pragma unroll 1
            for (int round = 0; round < nrounds; round++) {
                const G2Unit u = g2_unit(c, round);
                spin_ge(&g_cnt.hk[u.ks], u.nk * 64);
                if (round == 0) PROF(24);
                reader_fence();
                int k0 = u.kb0 * 64;
#pragma unroll 1
                for (int k = 0; k < u.nk; k++, k0 += 64) {
                    const uint32_t st = sbase + s * STAGE_BYTES, fb = bar_full + s * 8;
                    if (cnt >= 2) {
                        if (cnt >= NSTAGE) mbar_wait(bar_empty + s * 8, ph);
                        else if (cnt == NSTAGE - 1 && main_cta) mbar_wait(bar_prep, 0);
                        mbar_expect_tx(fb, 16384 + 24576);
                        tma3d(st + B_OFF, &mW1, fb, 0, k0, u.ft * 3);
                    }
                    tma3d(st, &mH, fb, 0, k0, u.dt * 2);
                    next();
                }
            }
            if (main_cta) {
                spin_ge(&g_cnt.cs[g1_g], 16);
                reader_fence();
                const uint8_t* img = g_wimg + (size_t)g1_g * 10 * 30720;
#pragma unroll 1
                for (int k = 0; k < 10; k++, img += 30720) {
                    const uint32_t st = sbase + s * STAGE_BYTES, fb = bar_full + s * 8;
                    mbar_wait(bar_empty + s * 8, ph);
                    mbar_expect_tx(fb, 16384 + 30720);
                    tma2d(st, &mX, fb, k * 64, g1_m * 128);
                    bulk_load(st + B_OFF, img, 30720, fb);
                    next();
                }
                PROF(25);
                const int dt0 = (f_n * 80) >> 7, dt1 = (f_n * 80 + 79) >> 7;
                spin_ge(&g_cnt.prep, 128);
                spin_ge(&g_cnt.gd[dt0], 24);
                spin_ge(&g_cnt.gd[dt1], 24);
                reader_fence();
#pragma unroll 1
                for (int j = 0; j < NSTAGE; j++) { mbar_wait(bar_empty + s * 8, ph); next(); }
                PROF(26);
                int fs = 0, fph = 1;
#pragma unroll 1
                for (int k = 0; k < F_NK; k++) {
                    const uint32_t st = sbase + fs * FSTAGE_BYTES, fb = bar_ff + fs * 8;
                    if (k == F_EARLY) mbar_wait(bar_stg, 0);
                    if (k == 24) { spin_ge(&g_cnt.gdl[dt0], 3); spin_ge(&g_cnt.gdl[dt1], 3); reader_fence(); }
                    if (k == 27) {
                        spin_ge(&g_cnt.o[f_m], 8);
                        reader_fence();
                        PROF(27);
                    }
                    if (k >= FSTAGE) mbar_wait(bar_fe + fs * 8, fph);
                    mbar_expect_tx(fb, 16384 + 10240);
                    if (k < 27) tma3d(st, &mW2, fb, 0, k * 64, f_m * 2);
                    else tma2d(st, &mO, fb, (k - 27) * 64, f_m * 128);
                    bulk_load(st + B_OFF, g_BF + (size_t)(f_n * 37 + k) * 10240, 10240, fb);
                    if (++fs == FSTAGE) { fs = 0; fph ^= 1; }
                }
            }
        }
      } else {
        const int atid = tid - 32;
        if (main_cta) {
            float* kz = &g_kvacc2[par ^ 1][0][0] + c * 216;
            for (int i = atid; i < 216; i += 96) kz[i] = 0.f;
            if (atid < 15) (&g_cs2[par ^ 1][0][0])[c * 15 + atid] = 0.f;
            if (atid == 32 && c < (int)(sizeof(Counters) / sizeof(Ctr))) ((Ctr*)&g_cnt2[par ^ 1])[c].v = 0;
        }
        if (main_cta) named_bar(7, 352);
        if (main_cta && atid == 0) {
            red_release(&g_cnt.cs[g1_g], 1);
            red_relaxed(&g_cnt.prep, 1);
            PROF(16);
            spin_ge(&g_cnt.cs[g1_g], 16);
            spin_ge(&g_cnt.hk[0], 704);
            spin_ge(&g_cnt.hk[1], 704);
            spin_ge(&g_cnt.hk[2], 640);
            reader_fence();
            mbar_expect_tx(bar_aux, 960 + 1024);
            bulk_load(sbase + SM_CS, &g_cs[g1_g][0], 960, bar_aux);
            bulk_load(sbase + SM_STATS, &g_stats[g1_m * 128], 1024, bar_aux);
            PROF(17);
            l2_prefetch((const uint8_t*)P.w2 + (size_t)c * 55296, 55296);
        }
#pragma unroll 1
        for (int round = 0; round < nrounds; round++) {
            const G2Unit u = g2_unit(c, round);
            if (atid < 32) {
                ((uint32_t*)(sgen + SM_B1))[atid] = __ldg((const uint32_t*)(P.b1 + u.ft * 192 + u.ks * 64) + atid);
                __syncwarp();
            }
            named_bar(3, 352);
            if (atid == 0) {
#pragma unroll 1
                for (int i = 0; i < 2; i++) {
                    int t3 = i + (i >= u.ks);
                    int slot = (u.ks > t3) ? u.ks - 1 : u.ks;
                    bulk_store(g_upart + (size_t)((u.tile * 3 + t3) * 2 + slot) * 2048, sbase + SM_X + i * 16384, 16384);
                }
                bulk_store_wait();
                red_relaxed(&g_cnt.uflag[u.tile], 1);
                spin_ge(&g_cnt.uflag[u.tile], 3);
                reader_fence();
                mbar_expect_tx(bar_x, 32768);
                bulk_load(sbase + SM_X, g_upart + (size_t)((u.tile * 3 + u.ks) * 2) * 2048, 32768, bar_x);
                PROF(18);
            }
            named_bar(4, 352);
            if (atid == 0) {
                {
                    const int kb = u.ft * 3 + u.ks;
                    int d = u.dt * 128;
                    const int dend = d + 128;
#pragma unroll 1
                    while (d < dend) {
                        const int n = d / 80, r = d - n * 80, cnt = min(80 - r, dend - d);
                        bulk_store(g_BF + (size_t)(n * 37 + kb) * 10240 + r * 128, sbase + SM_X + (d - u.dt * 128) * 128, cnt * 128);
                        d += cnt;
                    }
                }
                bulk_store_wait();
                red_relaxed(u.ft == 8 ? &g_cnt.gdl[u.dt] : &g_cnt.gd[u.dt], 1);
                mbar_arrive(bar_gs);
                PROF(19);
            }
        }
        if (main_cta) {
            named_bar(5, 352);
            if (atid == 0) {
                PROF(28);
                bulk_reduce_add_f32(&g_kvacc[g1_g][0], sbase + SM_KVF, KVF_BYTES);
                bulk_store_wait();
                red_relaxed(&g_cnt.kv[g1_g], 1);
                PROF(30);
                spin_ge(&g_cnt.kv[g1_g], 16);
                reader_fence();
                mbar_expect_tx(bar_kv, KVF_BYTES);
                bulk_load(sbase + SM_KVF, &g_kvacc[g1_g][0], KVF_BYTES, bar_kv);
                PROF(20);
            }
            named_bar(6, 352);
            if (atid == 0) {
                red_relaxed(&g_cnt.o[g1_m], 1);
                PROF(22);
                mbar_expect_tx(bar_xr, 20480);
                tma2d(sbase + SM_X, &mXr, bar_xr, f_n * 80, f_m * 128);
            }
        }
      }
    } else {
        reg_alloc<200>();
        const int ctid = tid - 128, wg = ctid >> 7, wp = (ctid >> 5) & 3, w8 = ctid >> 5;
        {
            float f[40];
    #pragma unroll
            for (int i = 0; i < 5; i++) {
                uint4 v = xv[i];
                f[8 * i] = bf_lo(v.x); f[8 * i + 1] = bf_hi(v.x); f[8 * i + 2] = bf_lo(v.y); f[8 * i + 3] = bf_hi(v.y);
                f[8 * i + 4] = bf_lo(v.z); f[8 * i + 5] = bf_hi(v.z); f[8 * i + 6] = bf_lo(v.w); f[8 * i + 7] = bf_hi(v.w);
            }
            auto hsum = [](float v) {
    #pragma unroll
                for (int o = 8; o > 0; o >>= 1) v += __shfl_xor_sync(0xffffffffu, v, o);
                return v;
            };
            float s = 0.f;
    #pragma unroll
            for (int i = 0; i < 40; i++) s += f[i];
            if (tid == 128) PROFD(13, s);
            long long ck0 = clock64();
            const float mean = hsum(s) * (1.0f / D_);
            uint4 wv[5], ov[2];
            {
                const int ct = tid - 128;
#pragma unroll
                for (int i = 0; i < 5; i++) {
                    const int ch = ct + 256 * i, r = ch / 30, ci = ch % 30;
                    if (ch < 1200) wv[i] = __ldg((const uint4*)(P.wqkv + (size_t)(g1_m * 40 + r) * 1920 + (ci / 10) * 640 + g1_g * 80 + (ci % 10) * 8));
                }
#pragma unroll
                for (int i = 0; i < 2; i++) {
                    const int ch = ct + 256 * i, r = ch / 10, ci = ch % 10;
                    if (ch < 400) ov[i] = __ldg((const uint4*)(P.wo + (size_t)((c >> 3) * 40 + r) * D_ + (c & 7) * 80 + ci * 8));
                }
            }
            const int ct = tid - 128;
            float q = 0.f;
    #pragma unroll
            for (int i = 0; i < 40; i++) { f[i] -= mean; q += f[i] * f[i]; }
            const float rstd = rsqrtf(hsum(q) * (1.0f / D_) + 1e-5f);
            s = 0.f;
    #pragma unroll
            for (int i = 0; i < 40; i += 2) {
                uint32_t p = pack_bf16(f[i] * rstd, f[i + 1] * rstd);
                f[i] = bf_lo(p); f[i + 1] = bf_hi(p);
                s += f[i] + f[i + 1];
            }
            const float mean2 = hsum(s) * (1.0f / D_);
            q = 0.f;
    #pragma unroll
            for (int i = 0; i < 40; i++) { f[i] -= mean2; q += f[i] * f[i]; }
            const float rstd2 = rsqrtf(hsum(q) * (1.0f / D_) + 1e-5f);
            uint4* hs = (uint4*)(sgen + SM_X + (ln_row & 15) * 1280);
#pragma unroll
            for (int i = 0; i < 5; i++) {
                uint4 v;
                v.x = pack_bf16(f[8 * i] * rstd2, f[8 * i + 1] * rstd2); v.y = pack_bf16(f[8 * i + 2] * rstd2, f[8 * i + 3] * rstd2);
                v.z = pack_bf16(f[8 * i + 4] * rstd2, f[8 * i + 5] * rstd2); v.w = pack_bf16(f[8 * i + 6] * rstd2, f[8 * i + 7] * rstd2);
                hs[hl + 16 * i] = v;
            }
            if (hl == 0) ((float2*)(sgen + SM_X + 20480))[ln_row & 15] = make_float2(mean, rstd);
            if (tid == 128) PROFD(14, rstd2);
            asm volatile("fence.proxy.async.shared::cta;" ::: "memory");
            named_bar(1, 256);
            if (tid == 128) {
                bulk_store(g_h + (size_t)c * 16 * D_, sbase + SM_X, 20480);
                bulk_store(g_stats + c * 16, sbase + SM_X + 20480, 128);
                bulk_store_wait();
                red_relaxed(&g_cnt.hk[c / 44], 16);
                PROF(33);
            }
            if (tid == 160) PROFD(34, __uint_as_float(wv[0].x ^ wv[4].x ^ ov[0].x));
            uint8_t* wq_s = sgen + (NSTAGE - 1) * STAGE_BYTES;
            __nv_bfloat16* wo_s = (__nv_bfloat16*)(sgen + (NSTAGE - 1) * STAGE_BYTES + 19200);
#pragma unroll
            for (int i = 0; i < 5; i++) {
                const int ch = ct + 256 * i, r = ch / 30, ci = ch % 30;
                if (ch < 1200) *(uint4*)(wq_s + (ci >> 1) * 1280 + r * 32 + (((ci & 1) ^ (((g1_m * 40 + r) >> 2) & 1)) << 4)) = wv[i];
            }
#pragma unroll
            for (int i = 0; i < 2; i++) {
                const int ch = ct + 256 * i;
                if (ch < 400) *(uint4*)(wo_s + ch * 8) = ov[i];
            }
            asm volatile("fence.proxy.async.shared::cta;" ::: "memory");
            if (tid == 160) PROF(35);
            named_bar(1, 256);
            if (tid == 160) PROF(36);
            if (ct >= 128 && ct < 143) {
                const int chk = ct - 128, k0 = g1_m * 40, kb = k0 >> 6, r0 = k0 & 63, n0 = min(40, 64 - r0);
                uint8_t* dst = g_wimg + (size_t)(g1_g * 10 + kb) * 30720 + chk * 2048;
                bulk_store(dst + r0 * 32, sbase + (NSTAGE - 1) * STAGE_BYTES + chk * 1280, n0 * 32);
                if (n0 < 40) bulk_store(dst + 30720, sbase + (NSTAGE - 1) * STAGE_BYTES + chk * 1280 + n0 * 32, (40 - n0) * 32);
                asm volatile("cp.async.bulk.commit_group;" ::: "memory");
            }
            if (ct < 120) {
                const int col = 2 * ct, chk = col >> 4, h16 = (col >> 3) & 1;
                const uint8_t* src = wq_s + chk * 1280 + (col & 7) * 2;
                float s0 = 0.f, s1 = 0.f;
#pragma unroll 8
                for (int r = 0; r < 40; r++) {
                    uint32_t v = *(const uint32_t*)(src + r * 32 + ((h16 ^ (((g1_m * 40 + r) >> 2) & 1)) << 4));
                    s0 += bf_lo(v); s1 += bf_hi(v);
                }
                atomicAdd(&g_cs[g1_g][col], s0);
                atomicAdd(&g_cs[g1_g][col + 1], s1);
            }
            if (tid == 160) PROF(37);
#pragma unroll 1
            for (int un = ct; un < 400; un += 256) {
                const int d = un / 5, j = un % 5;
                uint32_t w[4];
#pragma unroll
                for (int e = 0; e < 4; e++) {
                    uint32_t lo = *(const uint16_t*)(wo_s + (8 * j + 2 * e) * 80 + d), hi = *(const uint16_t*)(wo_s + (8 * j + 2 * e + 1) * 80 + d);
                    w[e] = lo | (hi << 16);
                }
                const int kk = (c >> 3) * 40 + 8 * j;
                *(uint4*)(g_BF + (size_t)((c & 7) * 37 + 27 + (kk >> 6)) * 10240 + d * 128 + ((((kk >> 3) & 7) ^ (d & 7)) << 4)) = make_uint4(w[0], w[1], w[2], w[3]);
            }
            if (ct >= 128 && ct < 143) asm volatile("cp.async.bulk.wait_group 0;" ::: "memory");
            if (tid == 160) PROF(38);
            named_bar(1, 256);
            if (tid == 160) PROF(39);
            if (ct == 0) mbar_arrive(bar_prep);
            named_arrive(7, 352);
        }
        if (ctid == 0) PROF(1);
        float acc[120], keep[32];
        int cs_ = 0, cph = 0;
        const bool wl = (ctid & 127) == 0;
        {
            const G2Unit u = g2_unit(c, 0);
            g2_run(u, true, sbase, sgen, ctid, cs_, cph, acc, keep);
#pragma unroll 1
            for (int k = 0; k < 10; k++) {
                mbar_wait(bar_full + cs_ * 8, cph);
                if (ctid == 0) PROF(48 + k);
                uint32_t st = sbase + cs_ * STAGE_BYTES;
                uint64_t da = desc_kmajor(st + wg * 8192), db = desc_mnmajor32(st + B_OFF);
                wg_fence();
#pragma unroll
                for (int kk = 0; kk < 4; kk++) wgmma_n240<0, 1>(acc, da + kk * 2, db + kk * 32, (k | kk) != 0);
                wg_commit();
                wg_wait<1>();
                if (k > 0 && wl) mbar_arrive(bar_empty + ((cs_ + NSTAGE - 1) % NSTAGE) * 8);
                if (++cs_ == NSTAGE) { cs_ = 0; cph ^= 1; }
                if (k == K_FIN) {
                    wg_wait<0>();
                    g2_fin(u, 0, sbase, sgen, ctid, keep);
                }
            }
            wg_wait<0>();
            if (wl) mbar_arrive(bar_empty + ((cs_ + NSTAGE - 1) % NSTAGE) * 8);
            if (ctid == 0) PROF(5);
            mbar_wait(bar_aux, 0);
            mbar_wait(bar_gs, 0);
            named_bar(1, 256);
            if (ctid == 0) PROF(6);
            const uint32_t pq_a = sbase + SM_X, pk_a = sbase + STG_OFF, v_a = pk_a + TILE_BYTES;
            {
                for (int j = ctid; j < KVF_BYTES / 16; j += 256) ((float4*)(sgen + SM_KVF))[j] = make_float4(0.f, 0.f, 0.f, 0.f);
                const float2* st_s = (const float2*)(sgen + SM_STATS);
                const uint32_t cs_a = launder(sbase) + SM_CS;
                const int r0 = wg * 64 + wp * 16 + (lane >> 2), cq = 2 * (lane & 3);
                const float2 s0 = st_s[r0], s1 = st_s[r0 + 8];
                const uint32_t off = (r0 * PQ_PITCH + cq) * 2;
#pragma unroll
                for (int part = 0; part < 2; part++) {
                    const uint32_t cs_b = launder(cs_a);
#pragma unroll
                    for (int jj = 0; jj < 10; jj++) {
                        const int j = ((part + 1) % 3) * 10 + jj;
                    const float2 cs = lds64_c(cs_b + (8 * j + cq) * 4);
                    float a0 = (acc[4 * j] - s0.x * cs.x) * s0.y, a1 = (acc[4 * j + 1] - s0.x * cs.y) * s0.y;
                    float a2 = (acc[4 * j + 2] - s1.x * cs.x) * s1.y, a3 = (acc[4 * j + 3] - s1.x * cs.y) * s1.y;
                    if (j < 20) {
                        a0 = fmaxf(a0, 0.f) + __expf(fminf(a0, 0.f)) + 1e-6f;
                        a1 = fmaxf(a1, 0.f) + __expf(fminf(a1, 0.f)) + 1e-6f;
                        a2 = fmaxf(a2, 0.f) + __expf(fminf(a2, 0.f)) + 1e-6f;
                        a3 = fmaxf(a3, 0.f) + __expf(fminf(a3, 0.f)) + 1e-6f;
                    }
                    const uint32_t dst = ((j < 10) ? pq_a : (j < 20) ? pk_a : v_a) + off + (j % 10) * 16;
                    sts32(dst, pack_bf16(a0, a1));
                    sts32(dst + 8 * PQ_PITCH * 2, pack_bf16(a2, a3));
                    }
                }
            }
            named_bar(1, 256);
            if (ctid == 0) PROF(7);
            {
                const int mt = (w8 == 0) ? 0 : (w8 <= 2) ? 1 : (w8 <= 4) ? 2 : (w8 <= 6) ? 3 : 4;
                const int n0 = (w8 == 0) ? 0 : (w8 == 1) ? 0 : (w8 == 2) ? 3 : (w8 == 3) ? 2 : (w8 == 4) ? 6 : (w8 == 5) ? 5 : (w8 == 6) ? 8 : 7;
                const int nn = (w8 == 0 || w8 == 1 || w8 == 5 || w8 == 7) ? 3 : (w8 == 3) ? 4 : 2;
                const bool doz = (w8 == 0 || w8 == 2 || w8 == 4 || w8 == 6 || w8 == 7);
                float cacc[5][4];
#pragma unroll
                for (int i = 0; i < 5; i++) { cacc[i][0] = cacc[i][1] = cacc[i][2] = cacc[i][3] = 0.f; }
                const int lr = lane & 7, lm = lane >> 3;
#pragma unroll 2
                for (int ks = 0; ks < 8; ks++) {
                    uint32_t a[4];
                    ldsm_x4_t(a, pk_a + ((ks * 16 + (lm >> 1) * 8 + lr) * PQ_PITCH + mt * 16 + (lm & 1) * 8) * 2);
#pragma unroll
                    for (int i = 0; i < 4; i++) {
                        uint32_t b[2];
                        ldsm_x2_t(b, v_a + ((ks * 16 + (lm & 1) * 8 + lr) * PQ_PITCH + min(n0 + i, 9) * 8) * 2);
                        mma16816(cacc[i], a, b[0], b[1]);
                    }
                    mma16816(cacc[4], a, 0x3F803F80u, 0x3F803F80u);
                }
                float* kvs = (float*)(sgen + SM_KVF);
                const int pbase = (mt == 0 ? 0 : mt == 1 ? 3 : mt == 2 ? 8 - 2 : mt == 3 ? 14 - 5 : 19 - 7);
                const int k8 = lane >> 2;
                const int sub = (k8 >> 1) * 4 + (k8 & 1);
#pragma unroll
                for (int i = 0; i < 4; i++) {
#pragma unroll
                    for (int e = 0; e < 4; e++) {
                        const int d = mt * 16 + k8 + (e >> 1) * 8, l4 = 2 * (lane & 3) + (e & 1), ec = (n0 + i) * 8 + l4;
                        if (i < nn && ec / 20 == d / 20) kvs[((pbase + n0 + i) * 32 + l4 * 4) * 4 + sub + (e >> 1) * 2] = cacc[i][e];
                    }
                }
                if (doz && (lane & 3) == 0) {
#pragma unroll
                    for (int h = 0; h < 2; h++) {
                        const int d = mt * 16 + k8 + h * 8;
                        kvs[((22 + mt) * 32 + (d / 20) * 4) * 4 + sub + h * 2] = cacc[4][2 * h];
                    }
                }
            }
            asm volatile("fence.proxy.async.shared::cta;" ::: "memory");
            named_arrive(5, 352);
            named_bar(8 + wg, 128);
            if ((ctid & 127) == 0) mbar_arrive(bar_stg);
            {
                const float2* st_s = (const float2*)(sgen + SM_STATS);
                const uint32_t cs_b = launder(sbase) + SM_CS;
                const int r0 = wg * 64 + wp * 16 + (lane >> 2), cq = 2 * (lane & 3);
                const float2 s0 = st_s[r0], s1 = st_s[r0 + 8];
                const uint32_t off = (r0 * PQ_PITCH + cq) * 2;
                const int part = 2;
#pragma unroll
                    for (int jj = 0; jj < 10; jj++) {
                        const int j = ((part + 1) % 3) * 10 + jj;
                    const float2 cs = lds64_c(cs_b + (8 * j + cq) * 4);
                    float a0 = (acc[4 * j] - s0.x * cs.x) * s0.y, a1 = (acc[4 * j + 1] - s0.x * cs.y) * s0.y;
                    float a2 = (acc[4 * j + 2] - s1.x * cs.x) * s1.y, a3 = (acc[4 * j + 3] - s1.x * cs.y) * s1.y;
                    if (j < 20) {
                        a0 = fmaxf(a0, 0.f) + __expf(fminf(a0, 0.f)) + 1e-6f;
                        a1 = fmaxf(a1, 0.f) + __expf(fminf(a1, 0.f)) + 1e-6f;
                        a2 = fmaxf(a2, 0.f) + __expf(fminf(a2, 0.f)) + 1e-6f;
                        a3 = fmaxf(a3, 0.f) + __expf(fminf(a3, 0.f)) + 1e-6f;
                    }
                    const uint32_t dst = ((j < 10) ? pq_a : (j < 20) ? pk_a : v_a) + off + (j % 10) * 16;
                    sts32(dst, pack_bf16(a0, a1));
                    sts32(dst + 8 * PQ_PITCH * 2, pack_bf16(a2, a3));
                    }
            }
            if (ctid == 0) PROF(8);
            const int fr0 = f_m * 128 + wg * 64 + wp * 16 + (lane >> 2);
            const uint32_t b2r0 = *(const uint16_t*)(P.b2 + fr0), b2r1 = *(const uint16_t*)(P.b2 + fr0 + 8);
            int fs = 0, fph = 0;
            float facc[40];
#pragma unroll 1
            for (int k = 0; k < 27; k++) {
                mbar_wait(bar_ff + fs * 8, fph);
                if (k == 0 && ctid == 0) PROF(9);
                uint32_t st = sbase + fs * FSTAGE_BYTES;
                uint64_t da = desc_mnmajor(st + wg * 8192), db = desc_kmajor(st + B_OFF);
                wg_fence();
#pragma unroll
                for (int kk = 0; kk < 4; kk++) wgmma_n80<1, 0>(facc, da + kk * 128, db + kk * 2, (k | kk) != 0);
                wg_commit();
                wg_wait<1>();
                if (k > 0 && wl) mbar_arrive(bar_fe + (fs == 0 ? FSTAGE - 1 : fs - 1) * 8);
                if (++fs == FSTAGE) { fs = 0; fph ^= 1; }
                if (k == 20 && ctid == 0) PROF(40);
                if (k == 26 && ctid == 0) PROF(41);
                if (k == K_O + 1 && ctid == 0) PROF(42);
                if (k == K_O) {
                    wg_wait<0>();
                    mbar_wait(bar_kv, 0);
                    if (ctid == 0) PROF(12);
                    const uint32_t kvf_s = launder(sbase) + SM_KVF + lane * 16;
                    const int lr = lane & 7, lm = lane >> 3, qd = lane & 3, ln4 = lane >> 2;
                    const int m0 = w8 * 16;
                    uint32_t a[5][4];
#pragma unroll
                    for (int kk = 0; kk < 5; kk++) ldsm_x4(a[kk], pq_a + ((m0 + (lm & 1) * 8 + lr) * PQ_PITCH + kk * 16 + (lm >> 1) * 8) * 2);
                    float den[4] = {0.f, 0.f, 0.f, 0.f};
#pragma unroll
                    for (int kk = 0; kk < 5; kk++) { float4 b = lds128_c(kvf_s + (22 + kk) * 512); mma16816(den, a[kk], pack_bf16(b.x, b.y), pack_bf16(b.z, b.w)); }
                    float dn[4][2];
#pragma unroll
                    for (int h = 0; h < 4; h++) {
                        int src = (lane & ~3) | (h >> 1);
                        float v0 = __shfl_sync(0xffffffffu, (h & 1) ? den[1] : den[0], src);
                        float v1 = __shfl_sync(0xffffffffu, (h & 1) ? den[3] : den[2], src);
                        dn[h][0] = __fdividef(1.0f, v0 + 1e-6f); dn[h][1] = __fdividef(1.0f, v1 + 1e-6f);
                    }
                    __syncwarp();
                    const uint32_t orow = pq_a + (m0 + ln4) * (PQ_PITCH * 2);
#pragma unroll
                    for (int nt = 0; nt < 10; nt++) {
                        float num[4] = {0.f, 0.f, 0.f, 0.f};
#pragma unroll
                        for (int kk = 0; kk < 5; kk++) {
                            const int first = kk == 0 ? 0 : kk == 1 ? 0 : kk == 2 ? 2 : kk == 3 ? 5 : 7;
                            const int cnt = kk == 0 ? 3 : kk == 1 ? 5 : kk == 2 ? 6 : kk == 3 ? 5 : 3;
                            const int off = kk == 0 ? 0 : kk == 1 ? 3 : kk == 2 ? 8 : kk == 3 ? 14 : 19;
                            if (nt >= first && nt < first + cnt) {
                                float4 b = lds128_c(kvf_s + (off + nt - first) * 512);
                                mma16816(num, a[kk], pack_bf16(b.x, b.y), pack_bf16(b.z, b.w));
                            }
                        }
                        const int oc = nt * 8 + 2 * qd;
                        const int h0 = oc / 20;
                        float d00 = h0 == 0 ? dn[0][0] : h0 == 1 ? dn[1][0] : h0 == 2 ? dn[2][0] : dn[3][0];
                        float d01 = h0 == 0 ? dn[0][1] : h0 == 1 ? dn[1][1] : h0 == 2 ? dn[2][1] : dn[3][1];
                        sts32(orow + oc * 2, pack_bf16(num[0] * d00, num[1] * d00));
                        sts32(orow + 8 * (PQ_PITCH * 2) + oc * 2, pack_bf16(num[2] * d01, num[3] * d01));
                    }
                    asm volatile("fence.proxy.async.shared::cta;" ::: "memory");
                    __syncwarp();
                    if (lane < 16) {
                        bulk_store(g_o + (size_t)(g1_m * 128 + m0 + lane) * D_ + g1_g * 80, pq_a + (m0 + lane) * (PQ_PITCH * 2), 160);
                        bulk_store_wait();
                    }
                    __syncwarp();
                    named_arrive(6, 352);
                }
            }
#pragma unroll 1
            for (int k = 27; k < F_NK; k++) {
                mbar_wait(bar_ff + fs * 8, fph);
                uint32_t st = sbase + fs * FSTAGE_BYTES;
                uint64_t da = desc_kmajor(st + wg * 8192), db = desc_kmajor(st + B_OFF);
                wg_fence();
#pragma unroll
                for (int kk = 0; kk < 4; kk++) wgmma_n80<0, 0>(facc, da + kk * 2, db + kk * 2, 1);
                wg_commit();
                wg_wait<1>();
                if (wl) mbar_arrive(bar_fe + (fs == 0 ? FSTAGE - 1 : fs - 1) * 8);
                if (++fs == FSTAGE) { fs = 0; fph ^= 1; }
            }
            wg_wait<0>();
            if (ctid == 0) PROF(10);
            {
                const float bb0 = bf_lo(b2r0), bb1 = bf_lo(b2r1);
                mbar_wait(bar_xr, 0);
                uint32_t* xs = (uint32_t*)(sgen + SM_X + (wg * 64 + wp * 16 + (lane >> 2)) * 160 + (lane & 3) * 4);
#pragma unroll
                for (int q = 0; q < 10; q++) {
                    const uint32_t x0 = xs[4 * q], x1 = xs[8 * 40 + 4 * q];
                    xs[4 * q] = pack_bf16(facc[4 * q] + bf_lo(x0) + bb0, facc[4 * q + 1] + bf_hi(x0) + bb0);
                    xs[8 * 40 + 4 * q] = pack_bf16(facc[4 * q + 2] + bf_lo(x1) + bb1, facc[4 * q + 3] + bf_hi(x1) + bb1);
                }
                asm volatile("fence.proxy.async.shared::cta;" ::: "memory");
                named_bar(1, 256);
                if (ctid == 0) {
                    tma_store2d(&mOut, sbase + SM_X, f_n * 80, f_m * 128);
                    bulk_store_wait();
                }
                if (ctid == 0) PROF(11);
            }
        }
    }
    __syncthreads();
    if (tid == 0) atomicInc(&g_done, 263);
}

typedef CUresult (*EncodeFn)(CUtensorMap*, CUtensorMapDataType, cuuint32_t, void*, const cuuint64_t*, const cuuint64_t*, const cuuint32_t*,
                             const cuuint32_t*, CUtensorMapInterleave, CUtensorMapSwizzle, CUtensorMapL2promotion, CUtensorMapFloatOOBfill);

bool make_map(EncodeFn enc, CUtensorMap* m, const void* ptr, int rank, const cuuint64_t* dims, const cuuint64_t* strides, const cuuint32_t* box) {
    cuuint32_t es[3] = {1, 1, 1};
    return enc(m, CU_TENSOR_MAP_DATA_TYPE_BFLOAT16, rank, (void*)ptr, dims, strides, box, es, CU_TENSOR_MAP_INTERLEAVE_NONE,
               CU_TENSOR_MAP_SWIZZLE_128B, CU_TENSOR_MAP_L2_PROMOTION_L2_128B, CU_TENSOR_MAP_FLOAT_OOB_FILL_NONE) == CUDA_SUCCESS;
}

struct HostState {
    bool ready;
    const void* key[4];
    CUtensorMap mX, mH, mW1, mW2, mO, mXr, mOut;
};
HostState g_hs;

}

extern "C" void kernel_launch(void* const* d_in, const int* in_sizes, int n_in, void* d_out, int out_size) {
    const __nv_bfloat16* x = (const __nv_bfloat16*)d_in[0];
    const __nv_bfloat16* wqkv = (const __nv_bfloat16*)d_in[1];
    const __nv_bfloat16* wo = (const __nv_bfloat16*)d_in[2];
    const __nv_bfloat16* w1 = (const __nv_bfloat16*)d_in[4];
    const __nv_bfloat16* b1 = (const __nv_bfloat16*)d_in[5];
    const __nv_bfloat16* w2 = (const __nv_bfloat16*)d_in[6];
    const __nv_bfloat16* b2 = (const __nv_bfloat16*)d_in[7];
    HostState& hs = g_hs;
    if (!hs.ready || hs.key[0] != x || hs.key[1] != w1 || hs.key[2] != w2 || hs.key[3] != d_out) {
        void* fn = nullptr;
        cudaDriverEntryPointQueryResult qr;
        if (cudaGetDriverEntryPoint("cuTensorMapEncodeTiled", &fn, cudaEnableDefault, &qr) != cudaSuccess || !fn) return;
        EncodeFn enc = (EncodeFn)fn;
        void *ph, *po;
        cudaGetSymbolAddress(&ph, g_h); cudaGetSymbolAddress(&po, g_o);
        {
            cuuint64_t d[2] = {640, 2048}, s[1] = {1280}; cuuint32_t b[2] = {64, 128};
            make_map(enc, &hs.mX, x, 2, d, s, b);
            make_map(enc, &hs.mO, po, 2, d, s, b);
        }
        {
            cuuint64_t d[3] = {64, 2048, 10}, s[2] = {1280, 128}; cuuint32_t b[3] = {64, 64, 2};
            make_map(enc, &hs.mH, ph, 3, d, s, b);
        }
        {
            cuuint64_t d[3] = {64, 2048, 27}, s[2] = {3456, 128}; cuuint32_t b[3] = {64, 64, 3};
            make_map(enc, &hs.mW1, w1, 3, d, s, b);
        }
        {
            cuuint64_t d[3] = {64, 1728, 32}, s[2] = {4096, 128}; cuuint32_t b[3] = {64, 64, 2};
            make_map(enc, &hs.mW2, w2, 3, d, s, b);
        }
        {
            cuuint64_t d[2] = {640, 2048}, st[1] = {1280}; cuuint32_t b[2] = {80, 128}, es[2] = {1, 1};
            enc(&hs.mXr, CU_TENSOR_MAP_DATA_TYPE_BFLOAT16, 2, (void*)x, d, st, b, es, CU_TENSOR_MAP_INTERLEAVE_NONE, CU_TENSOR_MAP_SWIZZLE_NONE,
                CU_TENSOR_MAP_L2_PROMOTION_L2_128B, CU_TENSOR_MAP_FLOAT_OOB_FILL_NONE);
            enc(&hs.mOut, CU_TENSOR_MAP_DATA_TYPE_BFLOAT16, 2, d_out, d, st, b, es, CU_TENSOR_MAP_INTERLEAVE_NONE, CU_TENSOR_MAP_SWIZZLE_NONE,
                CU_TENSOR_MAP_L2_PROMOTION_L2_128B, CU_TENSOR_MAP_FLOAT_OOB_FILL_NONE);
        }
        cudaFuncSetAttribute(mega_kernel, cudaFuncAttributeMaxDynamicSharedMemorySize, SMEM_ALLOC);
        hs.key[0] = x; hs.key[1] = w1; hs.key[2] = w2; hs.key[3] = d_out;
        hs.ready = true;
    }
    Params P{x, wqkv, wo, b1, b2, w2, (__nv_bfloat16*)d_out};
    mega_kernel<<<132, 384, SMEM_ALLOC>>>(hs.mX, hs.mH, hs.mW1, hs.mW2, hs.mO, hs.mXr, hs.mOut, P);
}
```
